```python
import torch

def _softmax(x, axis=-1):
    return torch.softmax(x, dim=axis)

def _gelu(x):
    return torch.nn.functional.gelu(x, approximate='tanh')

def _silu(x):
    return torch.nn.functional.silu(x)

def _sigmoid(x):
    return torch.sigmoid(x)

def _layernorm(x, axis=-1, eps=1e-05):
    m = x.mean(dim=axis, keepdim=True)
    v = x.var(dim=axis, keepdim=True, unbiased=False)
    return (x - m) / torch.sqrt(v + eps)

def _scatter_add(tgt, idx, src, axis=0):
    return tgt.clone().index_add_(axis, idx, src)

def _segment_sum(src, seg, n):
    out = torch.zeros((n,) + src.shape[1:], dtype=src.dtype)
    return out.index_add_(0, seg, src)

def _pad(x, pw):
    flat = tuple((v for pair in reversed(pw) for v in pair))
    return torch.nn.functional.pad(x, flat)
kernel_name = 'adaLN_cond__softmax_full_mha__mixer_gmlp__prompt'

def setup_inputs():

    _w = lambda a: (lambda t: t.to(torch.bfloat16) if t.is_floating_point() else t)(torch.as_tensor(a))

    def _A_setup():
        B, S, D = (1, 2048, 512)
        return {'x': _w((lambda *s: torch.randn(*s, dtype=torch.bfloat16) * 0.05)(B, S, D)), 'wqkv': _w((lambda *s: torch.randn(*s, dtype=torch.bfloat16) * 0.05)(D, 3 * D)), 'wo': _w((lambda *s: torch.randn(*s, dtype=torch.bfloat16) * 0.05)(D, D))}
    _A_in = _A_setup()

    def _B_setup():
        B, S, D, F = (1, 2048, 512, 1376)
        Fh = F // 2
        return {'x': _w((lambda *s: torch.randn(*s, dtype=torch.bfloat16) * 0.05)(B, S, D)), 'w_in': _w((lambda *s: torch.randn(*s, dtype=torch.bfloat16) * 0.4)(D, 2 * Fh)), 'w_sp': _w(0.01 * (lambda *s: torch.randn(*s, dtype=torch.bfloat16) * 0.4)(S, S)), 'b_sp': _w(1.0 + 0.01 * (lambda *s: torch.randn(*s, dtype=torch.bfloat16) * 0.05)(S)), 'w_out': _w((lambda *s: torch.randn(*s, dtype=torch.bfloat16) * 0.05)(Fh, D))}
    _B_in = _B_setup()
    return {'A_x': _A_in['x'], 'A_wqkv': _A_in['wqkv'], 'A_wo': _A_in['wo'], 'B_x': _B_in['x'], 'B_w_in': _B_in['w_in'], 'B_w_sp': _B_in['w_sp'], 'B_b_sp': _B_in['b_sp'], 'B_w_out': _B_in['w_out'], 'c': _w((lambda *s: torch.randn(*s, dtype=torch.bfloat16) * 0.1)(1, 512) * 8.0), 'w_mod': _w((lambda *s: torch.randn(*s, dtype=torch.bfloat16) * 0.1)(512, 6 * 512) * 512 ** (-0.5) * 8.0)}

def reference(A_x, A_wqkv, A_wo, B_x, B_w_in, B_w_sp, B_b_sp, B_w_out, c, w_mod):

    def _A_ref(x, wqkv, wo):
        B, S, D = x.shape
        H = 32
        Dh = D // H
        qkv = (lambda x, *d: x.permute(*d))((x @ wqkv).reshape(B, S, 3, H, Dh), 2, 0, 3, 1, 4)
        q, k, v = (qkv[0], qkv[1], qkv[2])
        scale = Dh ** (-0.5)
        scores = torch.einsum('bhqd,bhkd->bhqk', q, k) * scale
        p = _softmax(scores, axis=-1)
        o = torch.einsum('bhqk,bhkd->bhqd', p, v)
        return (lambda x, *d: x.permute(*d))(o, 0, 2, 1, 3).reshape(B, S, D) @ wo

    def _B_ref(x, w_in, w_sp, b_sp, w_out):
        B, S, D = x.shape
        F = w_in.shape[-1]
        Fh = F // 2
        z = _gelu(torch.einsum('bsd,df->bsf', x, w_in))
        z1 = z[..., :Fh].clone()
        z2 = _layernorm(z[..., Fh:], axis=-1)
        g = torch.einsum('ts,bsf->btf', w_sp, z2) + b_sp[None, :, None]
        return torch.einsum('bsf,fd->bsd', z1 * g, w_out)
    x = A_x
    mod = (_silu(c) @ w_mod).reshape(c.shape[0], 6, 1, -1)
    sa, ca, ga, sb, cb, gb = (mod[:, 0].clone(), mod[:, 1].clone(), mod[:, 2].clone(), mod[:, 3].clone(), mod[:, 4].clone(), mod[:, 5].clone())
    h = _layernorm(x, axis=-1) * (1 + ca) + sa
    x = x + ga * _A_ref(h, A_wqkv, A_wo)
    h = _layernorm(x, axis=-1) * (1 + cb) + sb
    x = x + gb * _B_ref(h, B_w_in, B_w_sp, B_b_sp, B_w_out)
    return x
```

```cpp
#include <cuda_runtime.h>
#include <cuda_bf16.h>
#include <cuda.h>
#include <stdint.h>

typedef __nv_bfloat16 bf16;
#define SEQ 2048
#define DM 512
#define FH 688
#define SPIN_LIMIT (1 << 22)

__device__ __align__(128) bf16 g_mod[6 * DM];
__device__ __align__(128) uint32_t g_mbx[12 * SEQ];
__device__ __align__(128) bf16 g_win[8 * 2 * 8 * 11 * 512];
__device__ __align__(128) bf16 g_qkv[96 * 2 * SEQ * 8];
__device__ __align__(128) float g_nrm[96 * 128];
__device__ __align__(128) bf16 g_o[32 * 64 * 64 * 8];
__device__ __align__(128) bf16 g_x1[32 * 64 * 64 * 8];
__device__ __align__(128) float2 g_st1[8 * SEQ];
__device__ __align__(128) uint32_t g_z1[128 * 22 * 256];
__device__ __align__(128) bf16 g_z2[8 * 32 * 11 * 64 * 8];
__device__ __align__(128) uint2 g_st2[8 * SEQ];
__device__ __align__(128) bf16 g_u[32 * 88 * 64 * 8];

#define TSX 0
#define TSL(i)
#define TSB
#define TS(k, p)
#define TSC(k, p)
__device__ __forceinline__ uint32_t smem_u32(const void* p) { return (uint32_t)__cvta_generic_to_shared(p); }
__device__ __forceinline__ void mbar_init(uint32_t a, int c) { asm volatile("mbarrier.init.shared::cta.b64 [%0], %1;" ::"r"(a), "r"(c) : "memory"); }
__device__ __forceinline__ void mbar_expect(uint32_t a, uint32_t b) { asm volatile("mbarrier.arrive.expect_tx.shared::cta.b64 _, [%0], %1;" ::"r"(a), "r"(b) : "memory"); }
__device__ __forceinline__ void mbar_arrive(uint32_t a) { asm volatile("mbarrier.arrive.shared::cta.b64 _, [%0];" ::"r"(a) : "memory"); }
__device__ __forceinline__ void mbar_wait(uint32_t a, uint32_t ph) {
  uint32_t ok;
  asm volatile("{.reg .pred p; mbarrier.try_wait.parity.shared::cta.b64 p, [%1], %2; selp.u32 %0, 1, 0, p;}" : "=r"(ok) : "r"(a), "r"(ph) : "memory");
  if (ok) return;
#pragma unroll 1
  for (int it = 0; it < SPIN_LIMIT; it++) {
    asm volatile("{.reg .pred p; mbarrier.try_wait.parity.shared::cta.b64 p, [%1], %2; selp.u32 %0, 1, 0, p;}" : "=r"(ok) : "r"(a), "r"(ph) : "memory");
    if (ok) return;
  }
  __trap();
}
__device__ __forceinline__ void mbar_wait2(uint32_t a, uint32_t ph, uint32_t b) {
  uint32_t ok;
  asm volatile("{.reg .pred p, q; mbarrier.try_wait.parity.shared::cta.b64 p, [%1], %2; mbarrier.try_wait.parity.shared::cta.b64 q, [%3], 0; and.pred p, p, q; selp.u32 %0, 1, 0, p;}"
               : "=r"(ok) : "r"(a), "r"(ph), "r"(b) : "memory");
  if (ok) return;
  mbar_wait(a, ph); mbar_wait(b, 0);
}
__device__ __forceinline__ void fence_mbar_init() { asm volatile("fence.mbarrier_init.release.cluster;" ::: "memory"); }
__device__ __forceinline__ void fence_async_smem() { asm volatile("fence.proxy.async.shared::cta;" ::: "memory"); }
__device__ __forceinline__ void bulk_g2s(uint32_t dst, const void* src, uint32_t bytes, uint32_t bar) {
  asm volatile("cp.async.bulk.shared::cluster.global.mbarrier::complete_tx::bytes [%0], [%1], %2, [%3];" ::"r"(dst), "l"(src), "r"(bytes), "r"(bar) : "memory");
}
__device__ __forceinline__ void tma_2d(uint32_t dst, const CUtensorMap* tm, int c0, int c1, uint32_t bar) {
  asm volatile("cp.async.bulk.tensor.2d.shared::cluster.global.mbarrier::complete_tx::bytes [%0], [%1, {%3, %4}], [%2];" ::"r"(dst), "l"(tm), "r"(bar), "r"(c0), "r"(c1) : "memory");
}
__device__ __forceinline__ void prefetch_l2(const void* p, uint32_t bytes) { asm volatile("cp.async.bulk.prefetch.L2.global [%0], %1;" ::"l"(p), "r"(bytes) : "memory"); }
__device__ __forceinline__ void prefetch_tmap(const CUtensorMap* tm) { asm volatile("prefetch.tensormap [%0];" ::"l"(tm) : "memory"); }
__device__ __forceinline__ void pdl_wait() { asm volatile("griddepcontrol.wait;" ::: "memory"); }
__device__ __forceinline__ void pdl_launch() { asm volatile("griddepcontrol.launch_dependents;" ::: "memory"); }
__device__ __forceinline__ void wg_fence() { asm volatile("wgmma.fence.sync.aligned;" ::: "memory"); }
__device__ __forceinline__ void wg_commit() { asm volatile("wgmma.commit_group.sync.aligned;" ::: "memory"); }
template <int N> __device__ __forceinline__ void wg_wait() { asm volatile("wgmma.wait_group.sync.aligned %0;" ::"n"(N) : "memory"); }
template <int N> __device__ __forceinline__ void reg_fence(float (&d)[N]) {
#pragma unroll
  for (int i = 0; i < N; i++) asm volatile("" : "+f"(d[i])::"memory");
}
__device__ __forceinline__ void bar_sync(int id, int n) { asm volatile("bar.sync %0, %1;" ::"r"(id), "r"(n) : "memory"); }
__device__ __forceinline__ void bar_arrive(int id, int n) { asm volatile("bar.arrive %0, %1;" ::"r"(id), "r"(n) : "memory"); }
__device__ __forceinline__ uint64_t mk_desc(uint32_t addr, uint32_t lbo, uint32_t sbo, uint32_t swz) {
  return (uint64_t)((addr & 0x3FFFF) >> 4) | ((uint64_t)(lbo >> 4) << 16) | ((uint64_t)(sbo >> 4) << 32) | ((uint64_t)swz << 62);
}
__device__ __forceinline__ uint32_t pack_bf16(float lo, float hi) {
  uint32_t r; asm("cvt.rn.bf16x2.f32 %0, %1, %2;" : "=r"(r) : "f"(hi), "f"(lo)); return r;
}
__device__ __forceinline__ float bf_lo(uint32_t v) { return __uint_as_float(v << 16); }
__device__ __forceinline__ float bf_hi(uint32_t v) { return __uint_as_float(v & 0xFFFF0000u); }
__device__ __forceinline__ uint32_t fma_bf16x2(uint32_t a, uint32_t b, uint32_t c) {
  uint32_t r; asm("fma.rn.bf16x2 %0, %1, %2, %3;" : "=r"(r) : "r"(a), "r"(b), "r"(c)); return r;
}
__device__ __forceinline__ float ex2f(float x) { float r; asm("ex2.approx.ftz.f32 %0, %1;" : "=f"(r) : "f"(x)); return r; }
__device__ __forceinline__ float rcpf(float x) { float r; asm("rcp.approx.ftz.f32 %0, %1;" : "=f"(r) : "f"(x)); return r; }
__device__ __forceinline__ float tanhf_hw(float x) { float r; asm("tanh.approx.f32 %0, %1;" : "=f"(r) : "f"(x)); return r; }
__device__ __forceinline__ float gelu_tanh(float z) {
  float t = tanhf_hw(z * fmaf(z * z, 0.0356774081f, 0.7978845608f));
  float hz = 0.5f * z;
  return fmaf(hz, t, hz);
}
__device__ __forceinline__ uint4 ldg128(const void* p) { return __ldg((const uint4*)p); }
__device__ __forceinline__ void sts128(uint32_t a, uint4 v) { asm volatile("st.shared.v4.b32 [%0], {%1,%2,%3,%4};" ::"r"(a), "r"(v.x), "r"(v.y), "r"(v.z), "r"(v.w) : "memory"); }

__device__ __forceinline__ uint4 lds128(uint32_t a) { uint4 v; asm volatile("ld.shared.v4.b32 {%0,%1,%2,%3}, [%4];" : "=r"(v.x), "=r"(v.y), "=r"(v.z), "=r"(v.w) : "r"(a) : "memory"); return v; }
__device__ __forceinline__ void sts32(uint32_t a, uint32_t v) { asm volatile("st.shared.b32 [%0], %1;" ::"r"(a), "r"(v) : "memory"); }
__device__ __forceinline__ uint32_t lds32(uint32_t a) { uint32_t v; asm volatile("ld.shared.b32 %0, [%1];" : "=r"(v) : "r"(a) : "memory"); return v; }
__device__ __forceinline__ void ldsm4(uint32_t* r, uint32_t a) {
  asm volatile("ldmatrix.sync.aligned.m8n8.x4.shared.b16 {%0,%1,%2,%3}, [%4];" : "=r"(r[0]), "=r"(r[1]), "=r"(r[2]), "=r"(r[3]) : "r"(a) : "memory");
}
__device__ __forceinline__ void stsm4(uint32_t a, uint32_t r0, uint32_t r1, uint32_t r2, uint32_t r3) {
  asm volatile("stmatrix.sync.aligned.m8n8.x4.shared.b16 [%0], {%1,%2,%3,%4};" ::"r"(a), "r"(r0), "r"(r1), "r"(r2), "r"(r3) : "memory");
}
__device__ __forceinline__ void bulk_s2g(void* dst, uint32_t src, uint32_t bytes) {
  asm volatile("cp.async.bulk.global.shared::cta.bulk_group [%0], [%1], %2;" ::"l"(dst), "r"(src), "r"(bytes) : "memory");
}
__device__ __forceinline__ void bulk_commit_wait() {
  asm volatile("cp.async.bulk.commit_group;" ::: "memory");
  asm volatile("cp.async.bulk.wait_group 0;" ::: "memory");
}
__device__ __forceinline__ void mbx_put(uint32_t* p, uint32_t v) { asm volatile("st.relaxed.gpu.global.b32 [%0], %1;" ::"l"(p), "r"(max(~v, 1u)) : "memory"); }
__device__ __forceinline__ uint32_t mbx_ld(const uint32_t* p) { uint32_t v; asm volatile("ld.relaxed.gpu.global.b32 %0, [%1];" : "=r"(v) : "l"(p) : "memory"); return v; }
__device__ __forceinline__ uint4 mbx_ld4(const uint32_t* p) {
  uint4 v; asm volatile("ld.relaxed.gpu.global.v4.b32 {%0, %1, %2, %3}, [%4];" : "=r"(v.x), "=r"(v.y), "=r"(v.z), "=r"(v.w) : "l"(p) : "memory"); return v;
}
__device__ __forceinline__ float silu_bf(bf16 c) { float v = __bfloat162float(c); return __bfloat162float(__float2bfloat16(v / (1.f + __expf(-v)))); }
__device__ __forceinline__ void ln_frags(uint32_t (&F)[16], const uint32_t (&ad)[4], uint32_t cs, const uint32_t (&ln)[4]) {
#pragma unroll
  for (int kk = 0; kk < 4; kk++) ldsm4(F + 4 * kk, ad[kk]);
#pragma unroll
  for (int kk = 0; kk < 4; kk++) {
    uint4 m = lds128(cs + kk * 64);
    F[4 * kk] = fma_bf16x2(fma_bf16x2(F[4 * kk], ln[0], ln[1]), m.x, m.z);
    F[4 * kk + 1] = fma_bf16x2(fma_bf16x2(F[4 * kk + 1], ln[2], ln[3]), m.x, m.z);
    F[4 * kk + 2] = fma_bf16x2(fma_bf16x2(F[4 * kk + 2], ln[0], ln[1]), m.y, m.w);
    F[4 * kk + 3] = fma_bf16x2(fma_bf16x2(F[4 * kk + 3], ln[2], ln[3]), m.y, m.w);
  }
#pragma unroll
  for (int i = 0; i < 16; i++) asm volatile("" : "+r"(F[i])::"memory");
}
template <int H, int X, int N> __device__ __forceinline__ void xred(float (&v)[N], int lane) {
  const bool up = lane & X;
#pragma unroll
  for (int i = 0; i < H; i++) {
    float keep = up ? v[i + H] : v[i], send = up ? v[i] : v[i + H];
    v[i] = keep + __shfl_xor_sync(0xffffffffu, send, X);
  }
}

"+f"(d[0]), "+f"(d[1]), "+f"(d[2]), "+f"(d[3]), "+f"(d[4]), "+f"(d[5]), "+f"(d[6]), "+f"(d[7]), "+f"(d[8]), "+f"(d[9]), "+f"(d[10]), "+f"(d[11]),
"+f"(d[12]), "+f"(d[13]), "+f"(d[14]), "+f"(d[15]), "+f"(d[16]), "+f"(d[17]), "+f"(d[18]), "+f"(d[19]), "+f"(d[20]), "+f"(d[21]), "+f"(d[22]),
"+f"(d[23]), "+f"(d[24]), "+f"(d[25]), "+f"(d[26]), "+f"(d[27]), "+f"(d[28]), "+f"(d[29]), "+f"(d[30]), "+f"(d[31]), "+f"(d[32]), "+f"(d[33]),
"+f"(d[34]), "+f"(d[35]), "+f"(d[36]), "+f"(d[37]), "+f"(d[38]), "+f"(d[39]), "+f"(d[40]), "+f"(d[41]), "+f"(d[42]), "+f"(d[43])

#define QKV_SMEM (131072 + 4 * 24576 + 2048 + 512 + 128 + TSX)
__global__ void __launch_bounds__(288, 1) k_qkv(const bf16* __restrict__ x, const bf16* __restrict__ c, const bf16* __restrict__ wmod, const bf16* __restrict__ wqkv,
                                                const __grid_constant__ CUtensorMap tmX, const __grid_constant__ CUtensorMap tmW) {
  TS(1, 0);
  extern __shared__ __align__(1024) uint8_t smem_raw[];
  const uint32_t sA = smem_u32(smem_raw), sB = sA + 131072, sCS = sB + 98304, sRed = sCS + 2048;
  const uint32_t fullA = sRed + 512, fullB = fullA + 64, empty = fullB + 32;
  const int t = threadIdx.x, warp = __shfl_sync(0xffffffffu, t >> 5, 0), lane = t & 31;
  const int rb = blockIdx.x >> 3, ct = blockIdx.x & 7;
  pdl_launch();
  if (warp == 8) {
    auto loadA = [&](int kb) { mbar_expect(fullA + 8 * kb, 16384); tma_2d(sA + kb * 16384, &tmX, kb * 64, rb * 128, fullA + 8 * kb); };
    auto loadB = [&](int kb) {
      const int s = kb & 3;
      mbar_expect(fullB + 8 * s, 24576);
      for (int j = 0; j < 3; j++) tma_2d(sB + s * 24576 + j * 8192, &tmW, ct * 192 + j * 64, kb * 64, fullB + 8 * s);
    };
    if (lane == 0) {
      if (sA & 1023) __trap();
      for (int i = 0; i < 8; i++) mbar_init(fullA + 8 * i, 1);
      for (int i = 0; i < 4; i++) { mbar_init(fullB + 8 * i, 1); mbar_init(empty + 8 * i, 2); }
      fence_mbar_init();
      prefetch_l2(wqkv + blockIdx.x * 6144, 12288);
#define QE 3
      for (int kb = 0; kb < QE; kb++) { loadA(kb); loadB(kb); }
    }
    __syncwarp();
    bar_sync(1, 288);
    if (lane == 0) {
      for (int kb = QE; kb < 8; kb++) {
        loadA(kb);
        if (kb < 4) loadB(kb);
      }
      for (int kb = 4; kb < 8; kb++) { mbar_wait(empty + 8 * (kb & 3), 0); loadB(kb); }
    }
    return;
  }
  const int col0 = (blockIdx.x & 63) * 16, k0 = (blockIdx.x >> 6) * 256 + (t >> 1);
  const bf16 c0 = c[k0], c1 = c[k0 + 128];
  uint4 w[2], xv[2][2];
#pragma unroll
  for (int p = 0; p < 2; p++) w[p] = ldg128(wmod + (size_t)(k0 + p * 128) * 3072 + col0 + (t & 1) * 8);
  const int srow = rb * 128 + ct * 16 + warp * 2;
#pragma unroll
  for (int r = 0; r < 2; r++) { xv[r][0] = ldg128(x + (size_t)(srow + r) * DM + lane * 8); xv[r][1] = ldg128(x + (size_t)(srow + r) * DM + 256 + lane * 8); }
  if (t < 128) g_st2[blockIdx.x * 128 + t] = make_uint2(0xFFFFFFFFu, 0xFFFFFFFFu);
  {
    const float s0 = silu_bf(c0), s1 = silu_bf(c1);
    const uint32_t *q0 = (const uint32_t*)&w[0], *q1 = (const uint32_t*)&w[1];
    float acc[8];
#pragma unroll
    for (int i = 0; i < 4; i++) { acc[2 * i] = fmaf(s0, bf_lo(q0[i]), s1 * bf_lo(q1[i])); acc[2 * i + 1] = fmaf(s0, bf_hi(q0[i]), s1 * bf_hi(q1[i])); }
    TS(8, 0);
    xred<4, 8>(acc, lane);
    xred<2, 4>(acc, lane); xred<1, 2>(acc, lane);
    acc[0] += __shfl_xor_sync(0xffffffffu, acc[0], 16);
    if (lane < 16) sts32(sRed + warp * 64 + ((lane & 1) * 8 + (lane >> 1)) * 4, __float_as_uint(acc[0]));
    if (warp) bar_arrive(2, 256);
    else {
      bar_sync(2, 256);
      float v = 0.f;
#pragma unroll
      for (int i = 0; i < 4; i++) v += __uint_as_float(lds32(sRed + (lane >> 4) * 256 + i * 64 + (lane & 15) * 4));
      v += __shfl_xor_sync(0xffffffffu, v, 16);
#pragma unroll
      for (int i = 0; i < 4; i++) mbx_put(g_mbx + (i * 2 + (lane >> 4)) * 2048 + blockIdx.x * 16 + (lane & 15), __float_as_uint(v));
    }
  }
  TS(8, 3);
  {
    float sm[2], sq[2];
#pragma unroll
    for (int r = 0; r < 2; r++) {
      const uint32_t* u = (const uint32_t*)&xv[r][0];
      sm[r] = 0.f;
#pragma unroll
      for (int i = 0; i < 8; i++) sm[r] += bf_lo(u[i]) + bf_hi(u[i]);
    }
#pragma unroll
    for (int o = 16; o; o >>= 1) { sm[0] += __shfl_xor_sync(0xffffffffu, sm[0], o); sm[1] += __shfl_xor_sync(0xffffffffu, sm[1], o); }
#pragma unroll
    for (int r = 0; r < 2; r++) {
      const uint32_t* u = (const uint32_t*)&xv[r][0];
      sm[r] *= (1.f / DM); sq[r] = 0.f;
#pragma unroll
      for (int i = 0; i < 8; i++) { float a = bf_lo(u[i]) - sm[r], b = bf_hi(u[i]) - sm[r]; sq[r] = fmaf(a, a, sq[r]); sq[r] = fmaf(b, b, sq[r]); }
    }
#pragma unroll
    for (int o = 16; o; o >>= 1) { sq[0] += __shfl_xor_sync(0xffffffffu, sq[0], o); sq[1] += __shfl_xor_sync(0xffffffffu, sq[1], o); }
    if (lane < 8) {
      float rs = rsqrtf((lane & 1 ? sq[1] : sq[0]) * (1.f / DM) + 1e-5f);
      mbx_put(g_mbx + 8 * SEQ + srow * 4 + lane, pack_bf16(rs, -(lane & 1 ? sm[1] : sm[0]) * rs));
    }
  }
  TS(1, 1);
  const int q4 = lane & 3, r8 = lane >> 2;
  const int row = rb * 128 + warp * 16 + r8;
  uint32_t ln[4];
  {
    uint4 a, b;
    uint32_t d, e;
    const uint32_t *mp = g_mbx + ct * 2048 + t * 4, *rp = g_mbx + 8 * SEQ + (row >> 1) * 8 + (row & 1);
    int it = 0;
    do {
      a = mbx_ld4(mp); b = mbx_ld4(mp + 1024); d = mbx_ld(rp); e = mbx_ld(rp + 32);
      if (++it > SPIN_LIMIT) __trap();
    } while (__any_sync(0xffffffffu, !min(min(min(min(a.x, a.y), min(a.z, a.w)), min(min(b.x, b.y), min(b.z, b.w))), min(d, e))));
    const uint32_t o = sCS + ((t & 127) >> 2) * 64 + (t & 1) * 32 + (t & 2) * 2 + (t < 128 ? 8 : 0), one = t < 128 ? 0u : 0x3F803F80u;
    sts32(o, fma_bf16x2(pack_bf16(__uint_as_float(~a.x) + __uint_as_float(~b.x), __uint_as_float(~a.y) + __uint_as_float(~b.y)), 0x3F803F80u, one));
    sts32(o + 16, fma_bf16x2(pack_bf16(__uint_as_float(~a.z) + __uint_as_float(~b.z), __uint_as_float(~a.w) + __uint_as_float(~b.w)), 0x3F803F80u, one));
    ln[0] = __byte_perm(~d, 0, 0x1010); ln[1] = __byte_perm(~d, 0, 0x3232);
    ln[2] = __byte_perm(~e, 0, 0x1010); ln[3] = __byte_perm(~e, 0, 0x3232);
  }
  bar_sync(1, 288);
  TS(1, 3);
  float acc[96];
#pragma unroll
  for (int i = 0; i < 96; i++) acc[i] = 0.f;
  reg_fence(acc);
  uint32_t F0[16], F1[16], ad[4];
#pragma unroll
  for (int kk = 0; kk < 4; kk++) ad[kk] = sA + (warp * 16 + (lane & 15)) * 128 + (((kk * 2 + (lane >> 4)) ^ (lane & 7)) << 4);
  uint32_t cs = sCS + q4 * 16;
  const uint64_t dB = mk_desc(sB, 8192, 1024, 1);
  TSB; TS(8, 4); const long long tc0 = clock64();
  auto step = [&](uint32_t (&F)[16], int kb) {
    wg_wait<1>();
    if (kb >= 2 && kb < 6 && (t & 127) == 0) mbar_arrive(empty + 8 * (kb - 2));
    ln_frags(F, ad, cs, ln);
#pragma unroll
    for (int kk = 0; kk < 4; kk++) ad[kk] += 16384;
    cs += 256;
    mbar_wait2(fullB + 8 * (kb & 3), kb >> 2, fullA + 8 * min(kb + 1, 7));
    TSL(kb);
    bar_sync(3 + (warp >> 2), 256);
    wg_fence();
#pragma unroll
    for (int kk = 0; kk < 4; kk++) {
      wg_rs128_t(*(float(*)[64])acc, F[4 * kk], F[4 * kk + 1], F[4 * kk + 2], F[4 * kk + 3], dB + (kb & 3) * 1536 + kk * 128, 1);
      wg_rs64_t(*(float(*)[32])(acc + 64), F[4 * kk], F[4 * kk + 1], F[4 * kk + 2], F[4 * kk + 3], dB + (kb & 3) * 1536 + 1024 + kk * 128, 1);
    }
    wg_commit();
    if (kb < 7 || warp < 4) bar_arrive(4 - (warp >> 2), 256);
  };
  if (warp >= 4) bar_arrive(3, 256);
  mbar_wait(fullA, 0);
#pragma unroll 1
  for (int kb = 0; kb < 8; kb += 2) { step(F0, kb); step(F1, kb + 1); }
  wg_wait<0>();
  reg_fence(acc);
  TS(1, 4);
  const uint32_t st = sA + warp * 2048;
  float nr[24];
#pragma unroll
  for (int hs = 0; hs < 12; hs++) {
    const float sc = ct * 12 + hs < 32 ? 0.25f * 1.4426950408889634f : 1.f;
    float v[8];
#pragma unroll
    for (int i = 0; i < 8; i++) v[i] = acc[hs * 8 + i] * sc;
    stsm4(st + (hs >> 2) * 16384 + (hs & 3) * 512 + lane * 16, pack_bf16(v[0], v[1]), pack_bf16(v[2], v[3]), pack_bf16(v[4], v[5]), pack_bf16(v[6], v[7]));
    nr[hs * 2] = fmaf(v[0], v[0], fmaf(v[1], v[1], fmaf(v[4], v[4], v[5] * v[5])));
    nr[hs * 2 + 1] = fmaf(v[2], v[2], fmaf(v[3], v[3], fmaf(v[6], v[6], v[7] * v[7])));
  }
  fence_async_smem();
  __syncwarp();
  if (lane < 24) {
    bulk_s2g(g_qkv + ((size_t)(ct * 24 + lane) * SEQ + rb * 128 + warp * 16) * 8, st + (lane >> 3) * 16384 + (lane & 7) * 256, 256);
    asm volatile("cp.async.bulk.commit_group;" ::: "memory");
  }
  xred<12, 2>(nr, lane); xred<6, 1>(nr, lane);
  uint32_t m[3];
#pragma unroll
  for (int i = 0; i < 3; i++) m[i] = max(__float_as_uint(nr[2 * i]) & 0x7FFFFFFFu, __float_as_uint(nr[2 * i + 1]) & 0x7FFFFFFFu);
#pragma unroll
  for (int o = 4; o < 32; o <<= 1)
#pragma unroll
    for (int i = 0; i < 3; i++) m[i] = max(m[i], __shfl_xor_sync(0xffffffffu, m[i], o));
  if (r8 < 3) g_nrm[(ct * 12 + q4 * 3 + r8) * 128 + rb * 8 + warp] = __uint_as_float(r8 == 0 ? m[0] : r8 == 1 ? m[1] : m[2]);
  asm volatile("cp.async.bulk.wait_group 0;" ::: "memory");
  TS(1, 5);
}

__device__ __forceinline__ uint32_t exp2_pair_sw(float x0, float x1, uint32_t cm, uint32_t co) {
  float y0 = x0 + (65536.f + 127.f - 205.f / 128.f);
  float y1 = x1 + (65536.f + 496.f - 205.f / 128.f);
  uint32_t w = __float_as_uint(y1) * 65536u + __float_as_uint(y0);
  uint32_t m;
  asm("lop3.b32 %0, %1, %2, %3, 0xEA;" : "=r"(m) : "r"(w), "r"(cm), "r"(co));
  uint32_t p = fma_bf16x2(m, m, 0x40034003u);
  return w - m + p;
}
__device__ __forceinline__ uint32_t exp2_pair_hw(float x0, float x1) { return pack_bf16(ex2f(x0), ex2f(x1)); }
#define HW_MASK 0x2492u
#define ATT_SMEM (176 * 1040 + 1024 + TSX)
__device__ __forceinline__ uint64_t desc2(uint32_t lo, uint32_t hi) { uint64_t d; asm("mov.b64 %0, {%1, %2};" : "=l"(d) : "r"(lo), "r"(hi)); return d; }

template <int N> __device__ __forceinline__ void desc_add(uint64_t& d) {
  asm("{.reg .b32 lo, hi; mov.b64 {lo, hi}, %0; add.u32 lo, lo, %1; mov.b64 %0, {lo, hi};}" : "+l"(d) : "n"(N));
}
__device__ __forceinline__ void attn_store(float (&O)[12], bf16* op) {
  float r0 = 1.f / O[8], r1 = 1.f / O[10];
  *(uint32_t*)(op) = pack_bf16(O[0] * r0, O[1] * r0);
  *(uint32_t*)(op + 64) = pack_bf16(O[2] * r1, O[3] * r1);
  *(uint32_t*)(op + 512) = pack_bf16(O[4] * r0, O[5] * r0);
  *(uint32_t*)(op + 512 + 64) = pack_bf16(O[6] * r1, O[7] * r1);
}
struct AttOff { uint32_t k[2], v[8]; };
__device__ __forceinline__ void attn_fast(uint32_t sK, uint32_t sQ, uint32_t bar, bf16* op, bool first, const AttOff& off) {
  float S[32], O[12];
  uint32_t P0[16], P1[16];
#pragma unroll
  for (int i = 0; i < 12; i++) O[i] = 0.f;
#pragma unroll
  for (int i = 0; i < 32; i++) S[i] = 0.f;
  reg_fence(O); reg_fence(S);
  const uint32_t co = off.k[0] * (0x3F803F80u / 64);
  const uint64_t dQ = mk_desc(sQ, 8192, 128, 0);
  uint64_t dK[2], dV[8];
#pragma unroll
  for (int i = 0; i < 2; i++) dK[i] = mk_desc(sK, 32768, 128, 0) + off.k[i];
#pragma unroll
  for (int i = 0; i < 8; i++) dV[i] = mk_desc(sK + 65536, 128, 32768, 0) + off.v[i];
  wg_fence();
  wg_ss64(S, dQ, mk_desc(sK, 32768, 128, 0), 0);
  wg_commit();
  wg_commit();
  auto step = [&](uint32_t (&P)[16], int h, bool last) {
    wg_wait<1>();
    reg_fence(S);
#pragma unroll
    for (int j = 0; j < 16; j++) P[j] = (((HW_MASK) >> j) & 1) ? exp2_pair_hw(S[2 * j], S[2 * j + 1]) : exp2_pair_sw(S[2 * j], S[2 * j + 1], 0x007F007Fu, co);
    wg_fence();
    if (!last) {
      wg_ss64(S, dQ, dK[h], 0);
      desc_add<128>(dK[h]);
      wg_commit();
    }
#pragma unroll
    for (int kk = 0; kk < 4; kk++) { wg_rs24_t(O, P[4 * kk], P[4 * kk + 1], P[4 * kk + 2], P[4 * kk + 3], dV[h * 4 + kk], 1); desc_add<128>(dV[h * 4 + kk]); }
    wg_commit();
  };
#pragma unroll 1
  for (int c = 0; c < 4; c++) {
    if (first && c < 3) mbar_wait(bar + 8 * (c + 1), 0);
#pragma unroll 1
    for (int i = c == 3; i < 4; i++) {
      step(P0, 0, false);
      step(P1, 1, false);
    }
  }
  step(P0, 0, false);
  step(P1, 1, true);
  wg_wait<0>();
  reg_fence(O);
  attn_store(O, op);
}
__device__ __forceinline__ void attn_safe(uint32_t sK, uint32_t sQ, uint32_t bar, bf16* op) {
  float S[32], O[12];
  uint32_t P[16];
#pragma unroll
  for (int i = 0; i < 12; i++) O[i] = 0.f;
#pragma unroll
  for (int i = 0; i < 32; i++) S[i] = 0.f;
  float m0 = -INFINITY, m1 = -INFINITY;
  const uint64_t dQ = mk_desc(sQ, 8192, 128, 0), dK = mk_desc(sK, 32768, 128, 0), dV = mk_desc(sK + 65536, 128, 32768, 0);
#pragma unroll 1
  for (int i = 0; i < 32; i++) {
    mbar_wait(bar + 8 * (i >> 3), 0);
    reg_fence(S);
    wg_fence();
    wg_ss64(S, dQ, dK + i * 64, 0);
    wg_commit();
    wg_wait<0>();
    reg_fence(S);
    float a = m0, b = m1;
#pragma unroll
    for (int j = 0; j < 8; j++) { a = fmaxf(a, fmaxf(S[4 * j], S[4 * j + 1])); b = fmaxf(b, fmaxf(S[4 * j + 2], S[4 * j + 3])); }
    a = fmaxf(a, __shfl_xor_sync(0xffffffffu, a, 1)); b = fmaxf(b, __shfl_xor_sync(0xffffffffu, b, 1));
    a = fmaxf(a, __shfl_xor_sync(0xffffffffu, a, 2)); b = fmaxf(b, __shfl_xor_sync(0xffffffffu, b, 2));
    float f0 = m0 == a ? 1.f : ex2f(m0 - a), f1 = m1 == b ? 1.f : ex2f(m1 - b);
    m0 = a; m1 = b;
#pragma unroll
    for (int j = 0; j < 3; j++) { O[4 * j] *= f0; O[4 * j + 1] *= f0; O[4 * j + 2] *= f1; O[4 * j + 3] *= f1; }
#pragma unroll
    for (int j = 0; j < 8; j++) { P[2 * j] = exp2_pair_hw(S[4 * j] - a, S[4 * j + 1] - a); P[2 * j + 1] = exp2_pair_hw(S[4 * j + 2] - b, S[4 * j + 3] - b); }
    reg_fence(O);
    wg_fence();
#pragma unroll
    for (int kk = 0; kk < 4; kk++) wg_rs24_t(O, P[4 * kk], P[4 * kk + 1], P[4 * kk + 2], P[4 * kk + 3], dV + i * 64 + kk * 16, 1);
    wg_commit();
    wg_wait<0>();
    reg_fence(O);
  }
  attn_store(O, op);
}

__device__ __forceinline__ void side_job(uint32_t sm, const bf16* __restrict__ c, const bf16* __restrict__ wmod, const bf16* __restrict__ w_in) {
  const int t = threadIdx.x, j = blockIdx.x;
  sts32(sm + t * 4, __float_as_uint(silu_bf(c[t])));
  __syncthreads();
  float acc[8];
#pragma unroll
  for (int i = 0; i < 8; i++) acc[i] = 0.f;
  const bf16* wp = wmod + (size_t)(t >> 6) * 64 * 3072 + 1024 + j * 512 + (t & 63) * 8;
#pragma unroll 16
  for (int k = 0; k < 64; k++) {
    const uint4 w = ldg128(wp + k * 3072);
    const float s = __uint_as_float(lds32(sm + ((t >> 6) * 64 + k) * 4));
    const uint32_t* q = (const uint32_t*)&w;
#pragma unroll
    for (int i = 0; i < 4; i++) { acc[2 * i] = fmaf(s, bf_lo(q[i]), acc[2 * i]); acc[2 * i + 1] = fmaf(s, bf_hi(q[i]), acc[2 * i + 1]); }
  }
#pragma unroll
  for (int i = 0; i < 8; i++) sts32(sm + 2048 + (t >> 6) * 2048 + (i * 64 + (t & 63)) * 4, __float_as_uint(acc[i]));
  __syncthreads();
  float v = 0.f;
#pragma unroll
  for (int i = 0; i < 8; i++) v += __uint_as_float(lds32(sm + 2048 + i * 2048 + t * 4));
  v = __bfloat162float(__float2bfloat16(v));
  g_mod[1024 + j * 512 + (t & 63) * 8 + (t >> 6)] = __float2bfloat16(j == 2 ? v + 1.f : v);
  for (int kb = 2 * j; kb < 2 * j + 2; kb++) {
    __syncthreads();
#pragma unroll 11
    for (int i = t; i < 64 * 176; i += 512) {
      const int k = i / 176, ch = i - k * 176;
      sts128(sm + ch * 1040 + k * 16, ch < 172 ? ldg128(w_in + (size_t)(kb * 64 + k) * (2 * FH) + ch * 8) : make_uint4(0, 0, 0, 0));
    }
    fence_async_smem();
    __syncthreads();
    if (t < 176) {
      const int h = t >= 88, f = t - h * 88, ct = f / 11;
      bulk_s2g(g_win + (((ct * 2 + h) * 8 + kb) * 11 + f - ct * 11) * 512, sm + (f < 86 ? f + (h ? 0 : 86) : 172) * 1040, 1024);
      bulk_commit_wait();
    }
  }
}

__global__ void __launch_bounds__(512, 1) k_attn(const bf16* __restrict__ c, const bf16* __restrict__ wmod, const bf16* __restrict__ w_in, const bf16* __restrict__ w_sp, const bf16* __restrict__ w_out, const bf16* __restrict__ wo, const __grid_constant__ AttOff off) {
  TS(2, 0);
  extern __shared__ uint8_t smem_raw[];
  __shared__ __align__(8) uint64_t bars[4];
  __shared__ __align__(16) uint32_t s_nrm[288];
  const uint32_t sK = (smem_u32(smem_raw) + 1023) & ~1023u, sQ = sK + 65536 + 98304;
  const uint32_t bar = smem_u32(bars);
  const int t = threadIdx.x, warp = __shfl_sync(0xffffffffu, t >> 5, 0), lane = t & 31;
  if (blockIdx.x < 4) { pdl_launch(); side_job(sK, c, wmod, w_in); TS(2, 5); return; }
  const int bid = blockIdx.x - 4, head = bid >> 2, quarter = bid & 3;
  if (t == 0) {
    for (int i = 0; i < 4; i++) mbar_init(bar + 8 * i, 1);
    fence_mbar_init();
    for (int i = 0; i < 4; i++) mbar_expect(bar + 8 * i, i == 0 ? 49152 + 1152 : 32768);
  }
#pragma unroll
  for (int i = 0; i < 4; i++) sts128(sK + 131072 + i * 8192 + t * 16, make_uint4(0x3F803F80u, 0x3F803F80u, 0x3F803F80u, 0x3F803F80u));
  fence_async_smem();
  __syncthreads();
  TS(2, 1);
  pdl_wait();
  pdl_launch();
  TS(2, 2);
  if (t == 0) {
    const bf16* qp = g_qkv + head * (2 * SEQ * 8) + quarter * 4096;
    const bf16* kp = g_qkv + (32 + head) * (2 * SEQ * 8);
    const bf16* vp = g_qkv + (64 + head) * (2 * SEQ * 8);
    bulk_g2s(smem_u32(s_nrm), g_nrm + (32 + head) * 128, 512, bar);
    bulk_g2s(smem_u32(s_nrm) + 512, g_nrm + (64 + head) * 128, 512, bar);
    bulk_g2s(smem_u32(s_nrm) + 1024, g_nrm + head * 128 + quarter * 32, 128, bar);
    bulk_g2s(sQ, qp, 8192, bar);
    bulk_g2s(sQ + 8192, qp + SEQ * 8, 8192, bar);
    for (int c = 0; c < 4; c++) {
      bulk_g2s(sK + c * 8192, kp + c * 4096, 8192, bar + 8 * c);
      bulk_g2s(sK + 32768 + c * 8192, kp + SEQ * 8 + c * 4096, 8192, bar + 8 * c);
      bulk_g2s(sK + 65536 + c * 8192, vp + c * 4096, 8192, bar + 8 * c);
      bulk_g2s(sK + 98304 + c * 8192, vp + SEQ * 8 + c * 4096, 8192, bar + 8 * c);
    }
  }
  mbar_wait(bar, 0);
  if (t == 128) {
    int l = bid;
    if (l < 32) prefetch_l2(wo + l * 8192, 16384);
    else if (l < 75) prefetch_l2(w_out + (l - 32) * 8192, 16384);
    for (int i = 0; i < 4; i++) prefetch_l2(w_sp + (size_t)(l * 4 + i) * 8192, 16384);
  }
  if (t >= 256 && t < 304) *(uint4*)(g_mbx + bid * 192 + (t - 256) * 4) = make_uint4(0, 0, 0, 0);
  const uint4 nk = *(const uint4*)(s_nrm + lane * 4), nv = *(const uint4*)(s_nrm + 128 + lane * 4);
  const float mk = __uint_as_float(__reduce_max_sync(0xffffffffu, max(max(nk.x, nk.y), max(nk.z, nk.w))));
  const float mv = __uint_as_float(__reduce_max_sync(0xffffffffu, max(max(nv.x, nv.y), max(nv.z, nv.w))));
  const float mq = __uint_as_float(__reduce_max_sync(0xffffffffu, s_nrm[256 + lane]));
  const bool fast = (mq * mk <= 3900.f) && (mv <= 1e24f);
  const int wg = __shfl_sync(0xffffffffu, warp >> 2, 0);
  TS(2, 3); TSC(2, 0);
#pragma unroll 1
  for (int mt = 0; mt < 2; mt++) {
    const int rb64 = quarter * 8 + wg * 2 + mt, r = (warp & 3) * 16 + (lane >> 2);
    bf16* op = g_o + (rb64 * 64 + head * 2) * 512 + r * 8 + (lane & 3) * 2;
    const uint32_t sq = sQ + (wg * 2 + mt) * 1024;
    if (fast) attn_fast(sK, sq, bar, op, mt == 0, off);
    else attn_safe(sK, sq, bar, op);
  }
  TS(2, 5); TSC(2, 1);
}

#define OPJ_SMEM (65536 + 131072 + 1024 + TSX)
__global__ void __launch_bounds__(256, 1) k_oproj(const bf16* __restrict__ x, const __grid_constant__ CUtensorMap tmW) {
  TS(3, 0);
  extern __shared__ uint8_t smem_raw[];
  __shared__ __align__(8) uint64_t bars[8];
  const uint32_t sB = (smem_u32(smem_raw) + 1023) & ~1023u, sA = sB + 131072;
  const uint32_t full = smem_u32(bars);
  const int t = threadIdx.x, warp = __shfl_sync(0xffffffffu, t >> 5, 0), lane = t & 31, wg = warp >> 2;
  const int rb = blockIdx.x >> 2, ct = blockIdx.x & 3;
  if (t == 0) {
    for (int i = 0; i < 8; i++) mbar_init(full + 8 * i, 1);
    fence_mbar_init();
    for (int kb = 0; kb < 8; kb++) {
      mbar_expect(full + 8 * kb, 24576);
      tma_2d(sB + kb * 16384, &tmW, ct * 128, kb * 64, full + 8 * kb);
      tma_2d(sB + kb * 16384 + 8192, &tmW, ct * 128 + 64, kb * 64, full + 8 * kb);
    }
  }
  const int r = (warp & 3) * 16 + (lane >> 2), col0 = ct * 128 + wg * 64 + (lane & 3) * 2;
  uint32_t xr[16];
#pragma unroll
  for (int j = 0; j < 8; j++) {
    xr[2 * j] = __ldg((const uint32_t*)(x + (size_t)(rb * 64 + r) * DM + col0 + j * 8));
    xr[2 * j + 1] = __ldg((const uint32_t*)(x + (size_t)(rb * 64 + r + 8) * DM + col0 + j * 8));
  }
  TS(3, 1);
  pdl_wait();
  pdl_launch();
  TS(3, 2);
  if (t == 0)
    for (int kb = 0; kb < 8; kb++) bulk_g2s(sA + kb * 8192, g_o + rb * 32768 + kb * 4096, 8192, full + 8 * kb);
  uint32_t ga[8];
#pragma unroll
  for (int j = 0; j < 8; j++) ga[j] = *(const uint32_t*)(g_mod + 1024 + col0 + j * 8);
  __syncthreads();
  TS(3, 3);
  float acc[32];
  const uint64_t dA = mk_desc(sA, 1024, 128, 0), dB = mk_desc(sB + wg * 8192, 8192, 1024, 1);
#pragma unroll 1
  for (int kb = 0; kb < 8; kb++) {
    mbar_wait(full + 8 * kb, 0);
    wg_fence();
#pragma unroll
    for (int kk = 0; kk < 4; kk++) wg_ss64_t(acc, dA + kb * 512 + kk * 128, dB + kb * 1024 + kk * 128, (kb | kk) != 0);
    wg_commit();
  }
  wg_wait<0>();
  reg_fence(acc);
  TS(3, 4);
  bf16* dst = g_x1 + (rb * 64 + ct * 16 + wg * 8) * 512 + r * 8 + (lane & 3) * 2;
  float s0 = 0.f, s1 = 0.f;
#pragma unroll
  for (int j = 0; j < 8; j++) {
    uint32_t a = pack_bf16(fmaf(bf_lo(ga[j]), acc[4 * j], bf_lo(xr[2 * j])), fmaf(bf_hi(ga[j]), acc[4 * j + 1], bf_hi(xr[2 * j])));
    uint32_t b = pack_bf16(fmaf(bf_lo(ga[j]), acc[4 * j + 2], bf_lo(xr[2 * j + 1])), fmaf(bf_hi(ga[j]), acc[4 * j + 3], bf_hi(xr[2 * j + 1])));
    *(uint32_t*)(dst + j * 512) = a;
    *(uint32_t*)(dst + j * 512 + 64) = b;
    acc[4 * j] = bf_lo(a); acc[4 * j + 1] = bf_hi(a); acc[4 * j + 2] = bf_lo(b); acc[4 * j + 3] = bf_hi(b);
    s0 += acc[4 * j] + acc[4 * j + 1]; s1 += acc[4 * j + 2] + acc[4 * j + 3];
  }
  s0 += __shfl_xor_sync(0xffffffffu, s0, 1); s1 += __shfl_xor_sync(0xffffffffu, s1, 1);
  s0 += __shfl_xor_sync(0xffffffffu, s0, 2); s1 += __shfl_xor_sync(0xffffffffu, s1, 2);
  s0 *= (1.f / 64); s1 *= (1.f / 64);
  float q0 = 0.f, q1 = 0.f;
#pragma unroll
  for (int j = 0; j < 8; j++) {
    float a = acc[4 * j] - s0, b = acc[4 * j + 1] - s0, c = acc[4 * j + 2] - s1, d = acc[4 * j + 3] - s1;
    q0 = fmaf(a, a, fmaf(b, b, q0)); q1 = fmaf(c, c, fmaf(d, d, q1));
  }
  q0 += __shfl_xor_sync(0xffffffffu, q0, 1); q1 += __shfl_xor_sync(0xffffffffu, q1, 1);
  q0 += __shfl_xor_sync(0xffffffffu, q0, 2); q1 += __shfl_xor_sync(0xffffffffu, q1, 2);
  if ((lane & 3) == 0) {
    g_st1[(rb * 64 + r) * 8 + ct * 2 + wg] = make_float2(s0, q0);
    g_st1[(rb * 64 + r + 8) * 8 + ct * 2 + wg] = make_float2(s1, q1);
  }
  TS(3, 5);
}

#define WIN_SMEM (131072 + 4 * 24576 + 2048 + 128 + TSX)
__global__ void __launch_bounds__(288, 1) k_win() {
  TS(4, 0);
  extern __shared__ __align__(1024) uint8_t smem_raw[];
  const uint32_t sA = smem_u32(smem_raw), sB = sA + 131072, sCS = sB + 98304;
  const uint32_t fullA = sCS + 2048, fullB = fullA + 64, empty = fullB + 32;
  const int t = threadIdx.x, warp = __shfl_sync(0xffffffffu, t >> 5, 0), lane = t & 31;
  const int rb = blockIdx.x >> 3, ct = blockIdx.x & 7;
  auto loadB = [&](int kb) {
    const int s = kb & 3;
    mbar_expect(fullB + 8 * s, 22528);
    bulk_g2s(sB + s * 24576, g_win + (ct * 16 + kb) * 5632, 11264, fullB + 8 * s);
    bulk_g2s(sB + s * 24576 + 12288, g_win + (ct * 16 + 8 + kb) * 5632, 11264, fullB + 8 * s);
  };
  if (t == 256) {
    if (sA & 1023) __trap();
    for (int i = 0; i < 8; i++) mbar_init(fullA + 8 * i, 1);
    for (int i = 0; i < 4; i++) { mbar_init(fullB + 8 * i, 1); mbar_init(empty + 8 * i, 2); }
    fence_mbar_init();
    for (int kb = 0; kb < 4; kb++) loadB(kb);
    for (int kb = 0; kb < 8; kb++) mbar_expect(fullA + 8 * kb, 16384);
  }
  if (t < 256) {
    const uint32_t o = sCS + (t >> 3) * 64 + (t & 3) * 16 + ((t >> 2) & 1) * 4;
    sts32(o, *(const uint32_t*)(g_mod + 2048 + 2 * t)); sts32(o + 8, *(const uint32_t*)(g_mod + 1536 + 2 * t));
  }
  __syncthreads();
  TS(4, 1);
  pdl_wait();
  pdl_launch();
  TS(4, 2);
  if (warp == 8) {
    if (lane < 16) bulk_g2s(sA + lane * 8192, g_x1 + (rb * 2 + (lane & 1)) * 32768 + (lane >> 1) * 4096, 8192, fullA + 8 * (lane >> 1));
    if (lane == 0)
      for (int kb = 4; kb < 8; kb++) { mbar_wait(empty + 8 * (kb & 3), 0); loadB(kb); }
    return;
  }
  const int wg = warp >> 2, q4 = lane & 3;
  const int row = rb * 128 + warp * 16 + (lane >> 2);
  uint32_t ln[4];
#pragma unroll
  for (int h = 0; h < 2; h++) {
    float4 p = *(const float4*)(g_st1 + (row + 8 * h) * 8 + q4 * 2);
    float m = p.x + p.z;
    m += __shfl_xor_sync(0xffffffffu, m, 1); m += __shfl_xor_sync(0xffffffffu, m, 2);
    m *= 0.125f;
    float q = p.y + p.w + 64.f * ((p.x - m) * (p.x - m) + (p.z - m) * (p.z - m));
    q += __shfl_xor_sync(0xffffffffu, q, 1); q += __shfl_xor_sync(0xffffffffu, q, 2);
    float rs = rsqrtf(q * (1.f / DM) + 1e-5f);
    ln[2 * h] = pack_bf16(rs, rs); ln[2 * h + 1] = pack_bf16(-m * rs, -m * rs);
  }
  TS(4, 3); TSC(4, 0);
  float acc[44], ac1[44];
#pragma unroll
  for (int i = 0; i < 44; i++) { acc[i] = 0.f; ac1[i] = 0.f; }
  reg_fence(acc); reg_fence(ac1);
  uint32_t F0[16], F1[16], ad[4];
#pragma unroll
  for (int kk = 0; kk < 4; kk++) ad[kk] = sA + wg * 8192 + (kk * 2 + (lane >> 4)) * 1024 + ((warp & 3) * 16 + (lane & 15)) * 16;
  uint32_t cs = sCS + q4 * 16;
  const uint64_t dB = mk_desc(sB, 128, 1024, 0);
  auto step = [&](uint32_t (&F)[16], int kb) {
    wg_wait<1>();
    if (kb >= 2 && kb < 6 && (t & 127) == 0) mbar_arrive(empty + 8 * (kb - 2));
    ln_frags(F, ad, cs, ln);
#pragma unroll
    for (int kk = 0; kk < 4; kk++) ad[kk] += 16384;
    cs += 256;
    mbar_wait2(fullB + 8 * (kb & 3), kb >> 2, fullA + 8 * min(kb + 1, 7));
    bar_sync(3 + (warp >> 2), 256);
    wg_fence();
#pragma unroll
    for (int kk = 0; kk < 4; kk++) {
      wg_rs88_t(acc, F[4 * kk], F[4 * kk + 1], F[4 * kk + 2], F[4 * kk + 3], dB + (kb & 3) * 1536 + kk * 16, 1);
      wg_rs88_t(ac1, F[4 * kk], F[4 * kk + 1], F[4 * kk + 2], F[4 * kk + 3], dB + (kb & 3) * 1536 + 768 + kk * 16, 1);
    }
    wg_commit();
    if (kb < 7 || warp < 4) bar_arrive(4 - (warp >> 2), 256);
  };
  if (warp >= 4) bar_arrive(3, 256);
  mbar_wait(fullA, 0);
#pragma unroll 1
  for (int kb = 0; kb < 8; kb += 2) { step(F0, kb); step(F1, kb + 1); }
  wg_wait<0>();
  reg_fence(acc); reg_fence(ac1);
  TS(4, 4); TSC(4, 1);
  const int nch = ct == 7 ? 9 : 11;
  const float cnt = (float)(nch * 8);
  float s0 = 0.f, s1 = 0.f;
#pragma unroll
  for (int j = 0; j < 11; j++) {
#pragma unroll
    for (int i = 0; i < 4; i++) acc[4 * j + i] = gelu_tanh(acc[4 * j + i]);
    s0 += acc[4 * j] + acc[4 * j + 1]; s1 += acc[4 * j + 2] + acc[4 * j + 3];
  }
  s0 += __shfl_xor_sync(0xffffffffu, s0, 1); s1 += __shfl_xor_sync(0xffffffffu, s1, 1);
  s0 += __shfl_xor_sync(0xffffffffu, s0, 2); s1 += __shfl_xor_sync(0xffffffffu, s1, 2);
  s0 /= cnt; s1 /= cnt;
  float q0 = 0.f, q1 = 0.f;
#pragma unroll
  for (int j = 0; j < 11; j++) {
    if (j < nch) {
      float a = acc[4 * j] - s0, b = acc[4 * j + 1] - s0, c = acc[4 * j + 2] - s1, d = acc[4 * j + 3] - s1;
      q0 = fmaf(a, a, fmaf(b, b, q0)); q1 = fmaf(c, c, fmaf(d, d, q1));
    }
  }
  q0 += __shfl_xor_sync(0xffffffffu, q0, 1); q1 += __shfl_xor_sync(0xffffffffu, q1, 1);
  q0 += __shfl_xor_sync(0xffffffffu, q0, 2); q1 += __shfl_xor_sync(0xffffffffu, q1, 2);
  if (q4 < 2) {
    uint32_t m = __float_as_uint(q4 ? s1 : s0), q = __float_as_uint(q4 ? q1 : q0) & 0x7FFFFFFFu;
    asm volatile("st.relaxed.gpu.global.v2.b32 [%0], {%1, %2};" ::"l"(g_st2 + (row + 8 * q4) * 8 + ct), "r"(m), "r"(q) : "memory");
  }
  uint32_t* z1p = g_z1 + blockIdx.x * (22 * 256) + t * 2;
#pragma unroll
  for (int j = 0; j < 11; j++) {
    uint2 v = make_uint2(pack_bf16(gelu_tanh(ac1[4 * j]), gelu_tanh(ac1[4 * j + 1])), pack_bf16(gelu_tanh(ac1[4 * j + 2]), gelu_tanh(ac1[4 * j + 3])));
    if (j >= nch) v = make_uint2(0, 0);
    *(uint2*)(z1p + j * 512) = v;
  }
  float mu2[2], rs2[2];
#pragma unroll
  for (int h = 0; h < 2; h++) {
    uint32_t a, b, c, d;
    const uint2* p = g_st2 + (row + 8 * h) * 8 + q4 * 2;
    int it = 0;
    do {
      asm volatile("ld.relaxed.gpu.global.v2.b32 {%0, %1}, [%2];" : "=r"(a), "=r"(b) : "l"(p) : "memory");
      asm volatile("ld.relaxed.gpu.global.v2.b32 {%0, %1}, [%2];" : "=r"(c), "=r"(d) : "l"(p + 1) : "memory");
      if (++it > SPIN_LIMIT) __trap();
    } while (b == 0xFFFFFFFFu || d == 0xFFFFFFFFu);
    float n1 = q4 == 3 ? 72.f : 88.f;
    float ma = __uint_as_float(a), mb = __uint_as_float(c);
    float m = 88.f * ma + n1 * mb;
    m += __shfl_xor_sync(0xffffffffu, m, 1); m += __shfl_xor_sync(0xffffffffu, m, 2);
    m *= (1.f / FH);
    float q = __uint_as_float(b) + __uint_as_float(d) + 88.f * (ma - m) * (ma - m) + n1 * (mb - m) * (mb - m);
    q += __shfl_xor_sync(0xffffffffu, q, 1); q += __shfl_xor_sync(0xffffffffu, q, 2);
    rs2[h] = rsqrtf(q * (1.f / FH) + 1e-5f); mu2[h] = -m * rs2[h];
  }
  bf16* z2p = g_z2 + ((ct * 32 + rb * 2 + wg) * 11) * 512 + ((warp & 3) * 16 + (lane >> 2)) * 8 + q4 * 2;
#pragma unroll
  for (int j = 0; j < 11; j++) {
    uint32_t a = pack_bf16(fmaf(acc[4 * j], rs2[0], mu2[0]), fmaf(acc[4 * j + 1], rs2[0], mu2[0]));
    uint32_t b = pack_bf16(fmaf(acc[4 * j + 2], rs2[1], mu2[1]), fmaf(acc[4 * j + 3], rs2[1], mu2[1]));
    if (j >= nch) { a = 0; b = 0; }
    *(uint32_t*)(z2p + j * 512) = a;
    *(uint32_t*)(z2p + j * 512 + 64) = b;
  }
  TS(4, 5);
}

#define SP_ST 8
#define SP_SMEM (SP_ST * (16384 + 11264) + 1024 + TSX)
__global__ void __launch_bounds__(288, 1) k_spatial(const bf16* __restrict__ b_sp, const __grid_constant__ CUtensorMap tmA) {
  TS(5, 0);
  extern __shared__ uint8_t smem_raw[];
  __shared__ __align__(8) uint64_t bars[2 * SP_ST];
  const uint32_t sA = (smem_u32(smem_raw) + 1023) & ~1023u, sB = sA + SP_ST * 16384;
  const uint32_t full = smem_u32(bars), empty = full + 8 * SP_ST;
  const int t = threadIdx.x, warp = __shfl_sync(0xffffffffu, t >> 5, 0), lane = t & 31;
  const int rb = blockIdx.x >> 3, ct = blockIdx.x & 7;
  pdl_launch();
  if (t == 256) {
    for (int i = 0; i < SP_ST; i++) { mbar_init(full + 8 * i, 1); mbar_init(empty + 8 * i, 2); }
    fence_mbar_init();
    for (int kb = 0; kb < SP_ST; kb++) { mbar_expect(full + 8 * kb, 16384 + 11264); tma_2d(sA + kb * 16384, &tmA, kb * 64, rb * 128, full + 8 * kb); }
  }
  __syncthreads();
  TS(5, 1);
  pdl_wait();
  TS(5, 2);
  if (warp == 8) {
    if (lane == 0) {
      const bf16* zp = g_z2 + ct * 32 * 5632;
      for (int kb = 0; kb < SP_ST; kb++) bulk_g2s(sB + kb * 11264, zp + kb * 5632, 11264, full + 8 * kb);
      int s = 0, ph = 0;
      for (int kb = SP_ST; kb < 32; kb++) {
        mbar_wait(empty + 8 * s, ph);
        mbar_expect(full + 8 * s, 16384 + 11264);
        tma_2d(sA + s * 16384, &tmA, kb * 64, rb * 128, full + 8 * s);
        bulk_g2s(sB + s * 11264, zp + kb * 5632, 11264, full + 8 * s);
        if (++s == SP_ST) { s = 0; ph ^= 1; }
      }
    }
    return;
  }
  const int wg = warp >> 2, q4 = lane & 3;
  const int row = rb * 128 + warp * 16 + (lane >> 2);
  uint2 z1[11];
  const uint32_t* z1p = g_z1 + blockIdx.x * (22 * 256) + t * 2;
#pragma unroll
  for (int j = 0; j < 11; j++) z1[j] = *(const uint2*)(z1p + j * 512);
  const float b0 = __bfloat162float(b_sp[row]), b1 = __bfloat162float(b_sp[row + 8]);
  TS(5, 3); TSC(5, 0);
  float acc[44];
  const uint64_t dA = mk_desc(sA + wg * 8192, 16, 1024, 1), dB = mk_desc(sB, 128, 1024, 0);
  int s = 0, ph = 0;
#pragma unroll 1
  for (int kb = 0; kb < 32; kb++) {
    mbar_wait(full + 8 * s, ph);
    wg_fence();
#pragma unroll
    for (int kk = 0; kk < 4; kk++) wg_ss88_t(acc, dA + s * 1024 + kk * 2, dB + s * 704 + kk * 16, (kb | kk) != 0);
    wg_commit();
    if (kb >= 1) { wg_wait<1>(); if ((t & 127) == 0) mbar_arrive(empty + 8 * (s == 0 ? SP_ST - 1 : s - 1)); }
    if (++s == SP_ST) { s = 0; ph ^= 1; }
  }
  wg_wait<0>();
  reg_fence(acc);
  TS(5, 4); TSC(5, 1);
  bf16* up = g_u + ((rb * 2 + wg) * 88 + ct * 11) * 512 + ((warp & 3) * 16 + (lane >> 2)) * 8 + q4 * 2;
#pragma unroll
  for (int j = 0; j < 11; j++) {
    *(uint32_t*)(up + j * 512) = pack_bf16((acc[4 * j] + b0) * bf_lo(z1[j].x), (acc[4 * j + 1] + b0) * bf_hi(z1[j].x));
    *(uint32_t*)(up + j * 512 + 64) = pack_bf16((acc[4 * j + 2] + b1) * bf_lo(z1[j].y), (acc[4 * j + 3] + b1) * bf_hi(z1[j].y));
  }
  TS(5, 5);
}

#define OUT_AST 5
#define OUT_SMEM (11 * 16384 + OUT_AST * 8192 + 1024 + TSX)
__global__ void __launch_bounds__(288, 1) k_out(bf16* __restrict__ out, const __grid_constant__ CUtensorMap tmW) {
  TS(6, 0);
  extern __shared__ uint8_t smem_raw[];
  __shared__ __align__(8) uint64_t bars[11 + OUT_AST];
  const uint32_t sB = (smem_u32(smem_raw) + 1023) & ~1023u, sA = sB + 11 * 16384;
  const uint32_t full = smem_u32(bars), empty = full + 88;
  const int t = threadIdx.x, warp = __shfl_sync(0xffffffffu, t >> 5, 0), lane = t & 31, wg = warp >> 2;
  const int rb = blockIdx.x >> 2, ct = blockIdx.x & 3;
  if (t == 256) {
    for (int i = 0; i < 11; i++) mbar_init(full + 8 * i, 1);
    for (int i = 0; i < OUT_AST; i++) mbar_init(empty + 8 * i, 2);
    fence_mbar_init();
    for (int kb = 0; kb < 11; kb++) {
      mbar_expect(full + 8 * kb, 24576);
      tma_2d(sB + kb * 16384, &tmW, ct * 128, kb * 64, full + 8 * kb);
      tma_2d(sB + kb * 16384 + 8192, &tmW, ct * 128 + 64, kb * 64, full + 8 * kb);
    }
  }
  __syncthreads();
  TS(6, 1);
  pdl_wait();
  TS(6, 2);
  if (warp == 8) {
    if (lane == 0) {
      int s = 0, ph = 1;
      for (int kb = 0; kb < 11; kb++) {
        if (kb >= OUT_AST) mbar_wait(empty + 8 * s, ph);
        bulk_g2s(sA + s * 8192, g_u + rb * (88 * 512) + kb * 4096, 8192, full + 8 * kb);
        if (++s == OUT_AST) { s = 0; ph ^= 1; }
      }
    }
    return;
  }
  const int r = (warp & 3) * 16 + (lane >> 2), col0 = ct * 128 + wg * 64 + (lane & 3) * 2;
  uint32_t xr[16], gb[8];
  const bf16* xp = g_x1 + (rb * 64 + ct * 16 + wg * 8) * 512 + r * 8 + (lane & 3) * 2;
#pragma unroll
  for (int j = 0; j < 8; j++) {
    xr[2 * j] = *(const uint32_t*)(xp + j * 512); xr[2 * j + 1] = *(const uint32_t*)(xp + j * 512 + 64);
    gb[j] = *(const uint32_t*)(g_mod + 2560 + col0 + j * 8);
  }
  TS(6, 3);
  float acc[32];
  const uint64_t dA = mk_desc(sA, 1024, 128, 0), dB = mk_desc(sB + wg * 8192, 8192, 1024, 1);
  int s = 0;
#pragma unroll 1
  for (int kb = 0; kb < 11; kb++) {
    mbar_wait(full + 8 * kb, 0);
    wg_fence();
#pragma unroll
    for (int kk = 0; kk < 4; kk++) wg_ss64_t(acc, dA + s * 512 + kk * 128, dB + kb * 1024 + kk * 128, (kb | kk) != 0);
    wg_commit();
    if (kb >= 1 && kb <= 11 - OUT_AST) { wg_wait<1>(); if ((t & 127) == 0) mbar_arrive(empty + 8 * (s == 0 ? OUT_AST - 1 : s - 1)); }
    if (++s == OUT_AST) s = 0;
  }
  wg_wait<0>();
  reg_fence(acc);
  TS(6, 4);
  bf16* dst = out + (size_t)(rb * 64 + r) * DM + col0;
#pragma unroll
  for (int j = 0; j < 8; j++) {
    *(uint32_t*)(dst + j * 8) = pack_bf16(fmaf(bf_lo(gb[j]), acc[4 * j], bf_lo(xr[2 * j])), fmaf(bf_hi(gb[j]), acc[4 * j + 1], bf_hi(xr[2 * j])));
    *(uint32_t*)(dst + 8 * DM + j * 8) = pack_bf16(fmaf(bf_lo(gb[j]), acc[4 * j + 2], bf_lo(xr[2 * j + 1])), fmaf(bf_hi(gb[j]), acc[4 * j + 3], bf_hi(xr[2 * j + 1])));
  }
  TS(6, 5);
}

typedef CUresult (*EncodeFn)(CUtensorMap*, CUtensorMapDataType, cuuint32_t, void*, const cuuint64_t*, const cuuint64_t*, const cuuint32_t*,
                             const cuuint32_t*, CUtensorMapInterleave, CUtensorMapSwizzle, CUtensorMapL2promotion, CUtensorMapFloatOOBfill);
static void make_map(EncodeFn fn, CUtensorMap* m, const void* p, uint64_t inner, uint64_t outer, uint32_t bi, uint32_t bo, CUtensorMapSwizzle sw = CU_TENSOR_MAP_SWIZZLE_128B) {
  cuuint64_t dims[2] = {inner, outer}, strides[1] = {inner * 2};
  cuuint32_t box[2] = {bi, bo}, es[2] = {1, 1};
  fn(m, CU_TENSOR_MAP_DATA_TYPE_BFLOAT16, 2, (void*)p, dims, strides, box, es, CU_TENSOR_MAP_INTERLEAVE_NONE, sw,
     CU_TENSOR_MAP_L2_PROMOTION_L2_256B, CU_TENSOR_MAP_FLOAT_OOB_FILL_NONE);
}
template <typename... KA, typename... A>
static void launch(void (*k)(KA...), int grid, int block, int smem, bool pdl, A... args) {
  cudaLaunchConfig_t cfg = {};
  cfg.gridDim = dim3(grid); cfg.blockDim = dim3(block); cfg.dynamicSmemBytes = smem; cfg.stream = cudaStreamPerThread;
  cudaLaunchAttribute at[1];
  at[0].id = cudaLaunchAttributeProgrammaticStreamSerialization; at[0].val.programmaticStreamSerializationAllowed = 1;
  cfg.attrs = at; cfg.numAttrs = pdl ? 1 : 0;
  cudaLaunchKernelEx(&cfg, k, args...);
}

extern "C" void kernel_launch(void* const* d_in, const int* in_sizes, int n_in, void* d_out, int out_size) {
  const bf16* x = (const bf16*)d_in[0]; const bf16* wqkv = (const bf16*)d_in[1]; const bf16* wo = (const bf16*)d_in[2];
  const bf16* w_in = (const bf16*)d_in[4]; const bf16* w_sp = (const bf16*)d_in[5]; const bf16* b_sp = (const bf16*)d_in[6];
  const bf16* w_out = (const bf16*)d_in[7]; const bf16* c = (const bf16*)d_in[8]; const bf16* w_mod = (const bf16*)d_in[9];
  static EncodeFn fn = nullptr;
  if (!fn) {
    cudaDriverEntryPointQueryResult qr;
    cudaGetDriverEntryPoint("cuTensorMapEncodeTiled", (void**)&fn, cudaEnableDefault, &qr);
    cudaFuncSetAttribute(k_qkv, cudaFuncAttributeMaxDynamicSharedMemorySize, QKV_SMEM);
    cudaFuncSetAttribute(k_attn, cudaFuncAttributeMaxDynamicSharedMemorySize, ATT_SMEM);
    cudaFuncSetAttribute(k_oproj, cudaFuncAttributeMaxDynamicSharedMemorySize, OPJ_SMEM);
    cudaFuncSetAttribute(k_win, cudaFuncAttributeMaxDynamicSharedMemorySize, WIN_SMEM);
    cudaFuncSetAttribute(k_spatial, cudaFuncAttributeMaxDynamicSharedMemorySize, SP_SMEM);
    cudaFuncSetAttribute(k_out, cudaFuncAttributeMaxDynamicSharedMemorySize, OUT_SMEM);
  }
  CUtensorMap mX, mQ, mO, mS, mW;
  make_map(fn, &mX, x, 512, 2048, 64, 128);
  make_map(fn, &mQ, wqkv, 1536, 512, 64, 64);
  make_map(fn, &mO, wo, 512, 512, 64, 64);
  make_map(fn, &mS, w_sp, 2048, 2048, 64, 128);
  make_map(fn, &mW, w_out, 512, FH, 64, 64);
  launch(k_qkv, 128, 288, QKV_SMEM, false, x, c, w_mod, wqkv, mX, mQ);
  AttOff off;
  for (int i = 0; i < 2; i++) off.k[i] = 64 * (i + 1);
  for (int i = 0; i < 8; i++) off.v[i] = 16 * i;
  launch(k_attn, 132, 512, ATT_SMEM, true, c, w_mod, w_in, w_sp, w_out, wo, off);
  launch(k_oproj, 128, 256, OPJ_SMEM, true, x, mO);
  launch(k_win, 128, 288, WIN_SMEM, true);
  launch(k_spatial, 128, 288, SP_SMEM, true, b_sp, mS);
  launch(k_out, 128, 288, OUT_SMEM, true, (bf16*)d_out, mW);
}
```

```cpp
#include <cuda_runtime.h>
#include <cuda_bf16.h>
#include <cuda.h>
#include <stdint.h>

typedef __nv_bfloat16 bf16;
#define SEQ 2048
#define DM 512
#define FH 688
#define SPIN_LIMIT (1 << 22)

__device__ __align__(128) bf16 g_mod[6 * DM];
__device__ __align__(128) uint32_t g_mbx[12 * SEQ];
__device__ __align__(128) bf16 g_win[8 * 2 * 8 * 11 * 512];
__device__ __align__(128) bf16 g_qkv[96 * 2 * SEQ * 8];
__device__ __align__(128) float g_nrm[96 * 128];
__device__ __align__(128) bf16 g_o[32 * 64 * 64 * 8];
__device__ __align__(128) bf16 g_x1[32 * 64 * 64 * 8];
__device__ __align__(128) float g_v[4 * 1408 * 2];
__device__ __align__(128) uint32_t g_flag[768];
__device__ __align__(128) uint32_t g_cnt[32];
__device__ __align__(128) bf16 g_z2[8 * 32 * 11 * 64 * 8];
__device__ __align__(128) uint2 g_st[2 * 8 * SEQ];
__device__ __align__(128) bf16 g_u[32 * 88 * 64 * 8];

#define TSX 0
#define TSL(i)
#define TSB
#define TSA(i)
#define TS(k, p)
#define TSC(k, p)
__device__ __forceinline__ uint32_t smem_u32(const void* p) { return (uint32_t)__cvta_generic_to_shared(p); }
__device__ __forceinline__ void mbar_init(uint32_t a, int c) { asm volatile("mbarrier.init.shared::cta.b64 [%0], %1;" ::"r"(a), "r"(c) : "memory"); }
__device__ __forceinline__ void mbar_expect(uint32_t a, uint32_t b) { asm volatile("mbarrier.arrive.expect_tx.shared::cta.b64 _, [%0], %1;" ::"r"(a), "r"(b) : "memory"); }
__device__ __forceinline__ void mbar_arrive(uint32_t a) { asm volatile("mbarrier.arrive.shared::cta.b64 _, [%0];" ::"r"(a) : "memory"); }
__device__ __forceinline__ void mbar_wait(uint32_t a, uint32_t ph) {
  uint32_t ok;
  asm volatile("{.reg .pred p; mbarrier.try_wait.parity.shared::cta.b64 p, [%1], %2; selp.u32 %0, 1, 0, p;}" : "=r"(ok) : "r"(a), "r"(ph) : "memory");
  if (ok) return;
#pragma unroll 1
  for (int it = 0; it < SPIN_LIMIT; it++) {
    asm volatile("{.reg .pred p; mbarrier.try_wait.parity.shared::cta.b64 p, [%1], %2; selp.u32 %0, 1, 0, p;}" : "=r"(ok) : "r"(a), "r"(ph) : "memory");
    if (ok) return;
  }
  __trap();
}
__device__ __forceinline__ void mbar_wait2(uint32_t a, uint32_t ph, uint32_t b) {
  uint32_t ok;
  asm volatile("{.reg .pred p, q; mbarrier.try_wait.parity.shared::cta.b64 p, [%1], %2; mbarrier.try_wait.parity.shared::cta.b64 q, [%3], 0; and.pred p, p, q; selp.u32 %0, 1, 0, p;}"
               : "=r"(ok) : "r"(a), "r"(ph), "r"(b) : "memory");
  if (ok) return;
  mbar_wait(a, ph); mbar_wait(b, 0);
}
__device__ __forceinline__ void fence_mbar_init() { asm volatile("fence.mbarrier_init.release.cluster;" ::: "memory"); }
__device__ __forceinline__ void fence_async_smem() { asm volatile("fence.proxy.async.shared::cta;" ::: "memory"); }
__device__ __forceinline__ void bulk_g2s(uint32_t dst, const void* src, uint32_t bytes, uint32_t bar) {
  asm volatile("cp.async.bulk.shared::cluster.global.mbarrier::complete_tx::bytes [%0], [%1], %2, [%3];" ::"r"(dst), "l"(src), "r"(bytes), "r"(bar) : "memory");
}
__device__ __forceinline__ void tma_2d(uint32_t dst, const CUtensorMap* tm, int c0, int c1, uint32_t bar) {
  asm volatile("cp.async.bulk.tensor.2d.shared::cluster.global.mbarrier::complete_tx::bytes [%0], [%1, {%3, %4}], [%2];" ::"r"(dst), "l"(tm), "r"(bar), "r"(c0), "r"(c1) : "memory");
}
__device__ __forceinline__ void prefetch_l2(const void* p, uint32_t bytes) { asm volatile("cp.async.bulk.prefetch.L2.global [%0], %1;" ::"l"(p), "r"(bytes) : "memory"); }
__device__ __forceinline__ void prefetch_tmap(const CUtensorMap* tm) { asm volatile("prefetch.tensormap [%0];" ::"l"(tm) : "memory"); }
__device__ __forceinline__ void pdl_wait() { asm volatile("griddepcontrol.wait;" ::: "memory"); }
__device__ __forceinline__ void pdl_launch() { asm volatile("griddepcontrol.launch_dependents;" ::: "memory"); }
__device__ __forceinline__ void wg_fence() { asm volatile("wgmma.fence.sync.aligned;" ::: "memory"); }
__device__ __forceinline__ void wg_commit() { asm volatile("wgmma.commit_group.sync.aligned;" ::: "memory"); }
template <int N> __device__ __forceinline__ void wg_wait() { asm volatile("wgmma.wait_group.sync.aligned %0;" ::"n"(N) : "memory"); }
template <int N> __device__ __forceinline__ void reg_fence(float (&d)[N]) {
#pragma unroll
  for (int i = 0; i < N; i++) asm volatile("" : "+f"(d[i])::"memory");
}
__device__ __forceinline__ void bar_sync(int id, int n) { asm volatile("bar.sync %0, %1;" ::"r"(id), "r"(n) : "memory"); }
__device__ __forceinline__ void bar_arrive(int id, int n) { asm volatile("bar.arrive %0, %1;" ::"r"(id), "r"(n) : "memory"); }
__device__ __forceinline__ uint64_t mk_desc(uint32_t addr, uint32_t lbo, uint32_t sbo, uint32_t swz) {
  return (uint64_t)((addr & 0x3FFFF) >> 4) | ((uint64_t)(lbo >> 4) << 16) | ((uint64_t)(sbo >> 4) << 32) | ((uint64_t)swz << 62);
}
__device__ __forceinline__ uint32_t pack_bf16(float lo, float hi) {
  uint32_t r; asm("cvt.rn.bf16x2.f32 %0, %1, %2;" : "=r"(r) : "f"(hi), "f"(lo)); return r;
}
__device__ __forceinline__ float bf_lo(uint32_t v) { return __uint_as_float(v << 16); }
__device__ __forceinline__ float bf_hi(uint32_t v) { return __uint_as_float(v & 0xFFFF0000u); }
__device__ __forceinline__ uint32_t fma_bf16x2(uint32_t a, uint32_t b, uint32_t c) {
  uint32_t r; asm("fma.rn.bf16x2 %0, %1, %2, %3;" : "=r"(r) : "r"(a), "r"(b), "r"(c)); return r;
}
__device__ __forceinline__ float ex2f(float x) { float r; asm("ex2.approx.ftz.f32 %0, %1;" : "=f"(r) : "f"(x)); return r; }
__device__ __forceinline__ float rcpf(float x) { float r; asm("rcp.approx.ftz.f32 %0, %1;" : "=f"(r) : "f"(x)); return r; }
__device__ __forceinline__ float tanhf_hw(float x) { float r; asm("tanh.approx.f32 %0, %1;" : "=f"(r) : "f"(x)); return r; }
__device__ __forceinline__ float gelu_tanh(float z) {
  float t = tanhf_hw(z * fmaf(z * z, 0.0356774081f, 0.7978845608f));
  float hz = 0.5f * z;
  return fmaf(hz, t, hz);
}
__device__ __forceinline__ uint4 ldg128(const void* p) { return __ldg((const uint4*)p); }
__device__ __forceinline__ void sts128(uint32_t a, uint4 v) { asm volatile("st.shared.v4.b32 [%0], {%1,%2,%3,%4};" ::"r"(a), "r"(v.x), "r"(v.y), "r"(v.z), "r"(v.w) : "memory"); }

__device__ __forceinline__ uint4 lds128(uint32_t a) { uint4 v; asm volatile("ld.shared.v4.b32 {%0,%1,%2,%3}, [%4];" : "=r"(v.x), "=r"(v.y), "=r"(v.z), "=r"(v.w) : "r"(a) : "memory"); return v; }
__device__ __forceinline__ void sts32(uint32_t a, uint32_t v) { asm volatile("st.shared.b32 [%0], %1;" ::"r"(a), "r"(v) : "memory"); }
__device__ __forceinline__ uint32_t lds32(uint32_t a) { uint32_t v; asm volatile("ld.shared.b32 %0, [%1];" : "=r"(v) : "r"(a) : "memory"); return v; }
__device__ __forceinline__ void ldsm4(uint32_t* r, uint32_t a) {
  asm volatile("ldmatrix.sync.aligned.m8n8.x4.shared.b16 {%0,%1,%2,%3}, [%4];" : "=r"(r[0]), "=r"(r[1]), "=r"(r[2]), "=r"(r[3]) : "r"(a) : "memory");
}
__device__ __forceinline__ void stsm4(uint32_t a, uint32_t r0, uint32_t r1, uint32_t r2, uint32_t r3) {
  asm volatile("stmatrix.sync.aligned.m8n8.x4.shared.b16 [%0], {%1,%2,%3,%4};" ::"r"(a), "r"(r0), "r"(r1), "r"(r2), "r"(r3) : "memory");
}
__device__ __forceinline__ void bulk_s2g(void* dst, uint32_t src, uint32_t bytes) {
  asm volatile("cp.async.bulk.global.shared::cta.bulk_group [%0], [%1], %2;" ::"l"(dst), "r"(src), "r"(bytes) : "memory");
}
__device__ __forceinline__ void bulk_commit_wait() {
  asm volatile("cp.async.bulk.commit_group;" ::: "memory");
  asm volatile("cp.async.bulk.wait_group 0;" ::: "memory");
}
__device__ __forceinline__ void mbx_put(uint32_t* p, uint32_t v) { asm volatile("st.relaxed.gpu.global.b32 [%0], %1;" ::"l"(p), "r"(max(~v, 1u)) : "memory"); }
__device__ __forceinline__ uint32_t mbx_ld(const uint32_t* p) { uint32_t v; asm volatile("ld.relaxed.gpu.global.b32 %0, [%1];" : "=r"(v) : "l"(p) : "memory"); return v; }
__device__ __forceinline__ uint4 mbx_ld4(const uint32_t* p) {
  uint4 v; asm volatile("ld.relaxed.gpu.global.v4.b32 {%0, %1, %2, %3}, [%4];" : "=r"(v.x), "=r"(v.y), "=r"(v.z), "=r"(v.w) : "l"(p) : "memory"); return v;
}
__device__ __forceinline__ void stat_put(uint2* p, float m, float q) {
  asm volatile("st.relaxed.gpu.global.v2.b32 [%0], {%1, %2};" ::"l"(p), "r"(__float_as_uint(m)), "r"(__float_as_uint(q) & 0x7FFFFFFFu) : "memory");
}
__device__ __forceinline__ void stat_get(const uint2* p, float n0, float n1, float inv, float (&rs)[2], float (&mr)[2]) {
  uint4 v[2];
  int it = 0;
  do {
    v[0] = mbx_ld4((const uint32_t*)p); v[1] = mbx_ld4((const uint32_t*)(p + 64));
    if (++it > SPIN_LIMIT) __trap();
  } while (__any_sync(0xffffffffu, (int)(v[0].y | v[0].w | v[1].y | v[1].w) < 0));
#pragma unroll
  for (int h = 0; h < 2; h++) {
    const float ma = __uint_as_float(v[h].x), mb = __uint_as_float(v[h].z);
    float m = n0 * ma + n1 * mb;
    m += __shfl_xor_sync(0xffffffffu, m, 1); m += __shfl_xor_sync(0xffffffffu, m, 2);
    m *= inv;
    float q = __uint_as_float(v[h].y) + __uint_as_float(v[h].w) + n0 * (ma - m) * (ma - m) + n1 * (mb - m) * (mb - m);
    q += __shfl_xor_sync(0xffffffffu, q, 1); q += __shfl_xor_sync(0xffffffffu, q, 2);
    rs[h] = rsqrtf(q * inv + 1e-5f); mr[h] = -m * rs[h];
  }
}
__device__ __forceinline__ float silu_bf(bf16 c) { float v = __bfloat162float(c); return __bfloat162float(__float2bfloat16(v / (1.f + __expf(-v)))); }
__device__ __forceinline__ void ln_frags(uint32_t (&F)[16], const uint32_t (&ad)[4], uint32_t cs, const uint32_t (&ln)[4]) {
#pragma unroll
  for (int kk = 0; kk < 4; kk++) ldsm4(F + 4 * kk, ad[kk]);
#pragma unroll
  for (int kk = 0; kk < 4; kk++) {
    uint4 m = lds128(cs + kk * 64);
    F[4 * kk] = fma_bf16x2(fma_bf16x2(F[4 * kk], ln[0], ln[1]), m.x, m.z);
    F[4 * kk + 1] = fma_bf16x2(fma_bf16x2(F[4 * kk + 1], ln[2], ln[3]), m.x, m.z);
    F[4 * kk + 2] = fma_bf16x2(fma_bf16x2(F[4 * kk + 2], ln[0], ln[1]), m.y, m.w);
    F[4 * kk + 3] = fma_bf16x2(fma_bf16x2(F[4 * kk + 3], ln[2], ln[3]), m.y, m.w);
  }
#pragma unroll
  for (int i = 0; i < 16; i++) asm volatile("" : "+r"(F[i])::"memory");
}
template <int H, int X, int N> __device__ __forceinline__ void xred(float (&v)[N], int lane) {
  const bool up = lane & X;
#pragma unroll
  for (int i = 0; i < H; i++) {
    float keep = up ? v[i + H] : v[i], send = up ? v[i] : v[i + H];
    v[i] = keep + __shfl_xor_sync(0xffffffffu, send, X);
  }
}

"+f"(d[0]), "+f"(d[1]), "+f"(d[2]), "+f"(d[3]), "+f"(d[4]), "+f"(d[5]), "+f"(d[6]), "+f"(d[7]), "+f"(d[8]), "+f"(d[9]), "+f"(d[10]), "+f"(d[11]),
"+f"(d[12]), "+f"(d[13]), "+f"(d[14]), "+f"(d[15]), "+f"(d[16]), "+f"(d[17]), "+f"(d[18]), "+f"(d[19]), "+f"(d[20]), "+f"(d[21]), "+f"(d[22]),
"+f"(d[23]), "+f"(d[24]), "+f"(d[25]), "+f"(d[26]), "+f"(d[27]), "+f"(d[28]), "+f"(d[29]), "+f"(d[30]), "+f"(d[31]), "+f"(d[32]), "+f"(d[33]),
"+f"(d[34]), "+f"(d[35]), "+f"(d[36]), "+f"(d[37]), "+f"(d[38]), "+f"(d[39]), "+f"(d[40]), "+f"(d[41]), "+f"(d[42]), "+f"(d[43])

#define QKV_SMEM (131072 + 4 * 24576 + 2048 + 512 + 128 + TSX)
__global__ void __launch_bounds__(288, 1) k_qkv(const bf16* __restrict__ x, const bf16* __restrict__ c, const bf16* __restrict__ wmod, const bf16* __restrict__ wqkv,
                                                const __grid_constant__ CUtensorMap tmX, const __grid_constant__ CUtensorMap tmW) {
  TS(1, 0);
  extern __shared__ __align__(1024) uint8_t smem_raw[];
  const uint32_t sA = smem_u32(smem_raw), sB = sA + 131072, sCS = sB + 98304, sRed = sCS + 2048;
  const uint32_t fullA = sRed + 512, fullB = fullA + 64, empty = fullB + 32;
  const int t = threadIdx.x, warp = __shfl_sync(0xffffffffu, t >> 5, 0), lane = t & 31;
  const int rb = blockIdx.x >> 3, ct = blockIdx.x & 7;
  pdl_launch();
  if (warp == 8) {
    auto loadA = [&](int kb) { mbar_expect(fullA + 8 * kb, 16384); tma_2d(sA + kb * 16384, &tmX, kb * 64, rb * 128, fullA + 8 * kb); };
    auto loadB = [&](int kb) {
      const int s = kb & 3;
      mbar_expect(fullB + 8 * s, 24576);
      for (int j = 0; j < 3; j++) tma_2d(sB + s * 24576 + j * 8192, &tmW, ct * 192 + j * 64, kb * 64, fullB + 8 * s);
    };
    if (lane == 0) {
      if (sA & 1023) __trap();
      for (int i = 0; i < 8; i++) mbar_init(fullA + 8 * i, 1);
      for (int i = 0; i < 4; i++) { mbar_init(fullB + 8 * i, 1); mbar_init(empty + 8 * i, 2); }
      fence_mbar_init();
      prefetch_l2(wqkv + blockIdx.x * 6144, 12288);
#define QE 3
      for (int kb = 0; kb < QE; kb++) { loadA(kb); loadB(kb); }
    }
    __syncwarp();
    bar_sync(1, 288);
    if (lane == 0) {
      for (int kb = QE; kb < 8; kb++) {
        loadA(kb);
        if (kb < 4) loadB(kb);
      }
      for (int kb = 4; kb < 8; kb++) { mbar_wait(empty + 8 * (kb & 3), 0); loadB(kb); }
    }
    return;
  }
  if (t == 0 && blockIdx.x == 0) g_cnt[0] = 0;
  const int col0 = (blockIdx.x & 63) * 16, k0 = (blockIdx.x >> 6) * 256 + (t >> 1);
  const bf16 c0 = c[k0], c1 = c[k0 + 128];
  uint4 w[2], xv[2][2];
#pragma unroll
  for (int p = 0; p < 2; p++) w[p] = ldg128(wmod + (size_t)(k0 + p * 128) * 3072 + col0 + (t & 1) * 8);
  const int srow = rb * 128 + ct * 16 + warp * 2;
#pragma unroll
  for (int r = 0; r < 2; r++) { xv[r][0] = ldg128(x + (size_t)(srow + r) * DM + lane * 8); xv[r][1] = ldg128(x + (size_t)(srow + r) * DM + 256 + lane * 8); }
  {
    const float s0 = silu_bf(c0), s1 = silu_bf(c1);
    const uint32_t *q0 = (const uint32_t*)&w[0], *q1 = (const uint32_t*)&w[1];
    float acc[8];
#pragma unroll
    for (int i = 0; i < 4; i++) { acc[2 * i] = fmaf(s0, bf_lo(q0[i]), s1 * bf_lo(q1[i])); acc[2 * i + 1] = fmaf(s0, bf_hi(q0[i]), s1 * bf_hi(q1[i])); }
    xred<4, 8>(acc, lane);
    xred<2, 4>(acc, lane); xred<1, 2>(acc, lane);
    acc[0] += __shfl_xor_sync(0xffffffffu, acc[0], 16);
    if (lane < 16) sts32(sRed + warp * 64 + ((lane & 1) * 8 + (lane >> 1)) * 4, __float_as_uint(acc[0]));
    if (warp) bar_arrive(2, 256);
    else {
      bar_sync(2, 256);
      float v = 0.f;
#pragma unroll
      for (int i = 0; i < 4; i++) v += __uint_as_float(lds32(sRed + (lane >> 4) * 256 + i * 64 + (lane & 15) * 4));
      v += __shfl_xor_sync(0xffffffffu, v, 16);
#pragma unroll
      for (int i = 0; i < 4; i++) mbx_put(g_mbx + (i * 2 + (lane >> 4)) * 2048 + blockIdx.x * 16 + (lane & 15), __float_as_uint(v));
    }
  }
  {
    float sm[2], sq[2];
#pragma unroll
    for (int r = 0; r < 2; r++) {
      const uint32_t* u = (const uint32_t*)&xv[r][0];
      sm[r] = 0.f;
#pragma unroll
      for (int i = 0; i < 8; i++) sm[r] += bf_lo(u[i]) + bf_hi(u[i]);
    }
#pragma unroll
    for (int o = 16; o; o >>= 1) { sm[0] += __shfl_xor_sync(0xffffffffu, sm[0], o); sm[1] += __shfl_xor_sync(0xffffffffu, sm[1], o); }
#pragma unroll
    for (int r = 0; r < 2; r++) {
      const uint32_t* u = (const uint32_t*)&xv[r][0];
      sm[r] *= (1.f / DM); sq[r] = 0.f;
#pragma unroll
      for (int i = 0; i < 8; i++) { float a = bf_lo(u[i]) - sm[r], b = bf_hi(u[i]) - sm[r]; sq[r] = fmaf(a, a, sq[r]); sq[r] = fmaf(b, b, sq[r]); }
    }
#pragma unroll
    for (int o = 16; o; o >>= 1) { sq[0] += __shfl_xor_sync(0xffffffffu, sq[0], o); sq[1] += __shfl_xor_sync(0xffffffffu, sq[1], o); }
    if (lane < 8) {
      float rs = rsqrtf((lane & 1 ? sq[1] : sq[0]) * (1.f / DM) + 1e-5f);
      mbx_put(g_mbx + 8 * SEQ + srow * 4 + lane, pack_bf16(rs, -(lane & 1 ? sm[1] : sm[0]) * rs));
    }
  }
  TS(1, 1);
  const int q4 = lane & 3, r8 = lane >> 2;
  const int row = rb * 128 + warp * 16 + r8;
  uint32_t ln[4];
  {
    uint4 a, b;
    uint32_t d, e;
    const uint32_t *mp = g_mbx + ct * 2048 + t * 4, *rp = g_mbx + 8 * SEQ + (row >> 1) * 8 + (row & 1);
    int it = 0;
    do {
      a = mbx_ld4(mp); b = mbx_ld4(mp + 1024); d = mbx_ld(rp); e = mbx_ld(rp + 32);
      if (++it > SPIN_LIMIT) __trap();
    } while (__any_sync(0xffffffffu, !min(min(min(min(a.x, a.y), min(a.z, a.w)), min(min(b.x, b.y), min(b.z, b.w))), min(d, e))));
    const uint32_t o = sCS + ((t & 127) >> 2) * 64 + (t & 1) * 32 + (t & 2) * 2 + (t < 128 ? 8 : 0), one = t < 128 ? 0u : 0x3F803F80u;
    sts32(o, fma_bf16x2(pack_bf16(__uint_as_float(~a.x) + __uint_as_float(~b.x), __uint_as_float(~a.y) + __uint_as_float(~b.y)), 0x3F803F80u, one));
    sts32(o + 16, fma_bf16x2(pack_bf16(__uint_as_float(~a.z) + __uint_as_float(~b.z), __uint_as_float(~a.w) + __uint_as_float(~b.w)), 0x3F803F80u, one));
    ln[0] = __byte_perm(~d, 0, 0x1010); ln[1] = __byte_perm(~d, 0, 0x3232);
    ln[2] = __byte_perm(~e, 0, 0x1010); ln[3] = __byte_perm(~e, 0, 0x3232);
  }
  bar_sync(1, 288);
  TS(1, 3);
  float acc[96];
#pragma unroll
  for (int i = 0; i < 96; i++) acc[i] = 0.f;
  reg_fence(acc);
  uint32_t F0[16], F1[16], ad[4];
#pragma unroll
  for (int kk = 0; kk < 4; kk++) ad[kk] = sA + (warp * 16 + (lane & 15)) * 128 + (((kk * 2 + (lane >> 4)) ^ (lane & 7)) << 4);
  uint32_t cs = sCS + q4 * 16;
  const uint64_t dB = mk_desc(sB, 8192, 1024, 1);
  const long long tc0 = clock64();
  auto step = [&](uint32_t (&F)[16], int kb) {
    wg_wait<1>();
    if (kb >= 2 && kb < 6 && (t & 127) == 0) mbar_arrive(empty + 8 * (kb - 2));
    ln_frags(F, ad, cs, ln);
#pragma unroll
    for (int kk = 0; kk < 4; kk++) ad[kk] += 16384;
    cs += 256;
    mbar_wait2(fullB + 8 * (kb & 3), kb >> 2, fullA + 8 * min(kb + 1, 7));
    bar_sync(3 + (warp >> 2), 256);
    wg_fence();
#pragma unroll
    for (int kk = 0; kk < 4; kk++) {
      wg_rs128_t(*(float(*)[64])acc, F[4 * kk], F[4 * kk + 1], F[4 * kk + 2], F[4 * kk + 3], dB + (kb & 3) * 1536 + kk * 128, 1);
      wg_rs64_t(*(float(*)[32])(acc + 64), F[4 * kk], F[4 * kk + 1], F[4 * kk + 2], F[4 * kk + 3], dB + (kb & 3) * 1536 + 1024 + kk * 128, 1);
    }
    wg_commit();
    if (kb < 7 || warp < 4) bar_arrive(4 - (warp >> 2), 256);
  };
  if (warp >= 4) bar_arrive(3, 256);
  mbar_wait(fullA, 0);
#pragma unroll 1
  for (int kb = 0; kb < 8; kb += 2) { step(F0, kb); step(F1, kb + 1); }
  wg_wait<0>();
  reg_fence(acc);
  TS(1, 4);
  uint32_t* qp = (uint32_t*)(g_qkv + ((size_t)ct * 24 * SEQ + rb * 128 + warp * 16) * 8) + lane;
  float nr[24];
#pragma unroll
  for (int hs = 0; hs < 12; hs++) {
    const float sc = ct * 12 + hs < 32 ? 0.25f * 1.4426950408889634f : 1.f;
    float v[8];
#pragma unroll
    for (int i = 0; i < 8; i++) v[i] = acc[hs * 8 + i] * sc;
#pragma unroll
    for (int i = 0; i < 4; i++) qp[(hs * 2 + (i >> 1)) * SEQ * 4 + (i & 1) * 32] = pack_bf16(v[2 * i], v[2 * i + 1]);
    nr[hs * 2] = fmaf(v[0], v[0], fmaf(v[1], v[1], fmaf(v[4], v[4], v[5] * v[5])));
    nr[hs * 2 + 1] = fmaf(v[2], v[2], fmaf(v[3], v[3], fmaf(v[6], v[6], v[7] * v[7])));
  }
  xred<12, 2>(nr, lane); xred<6, 1>(nr, lane);
  uint32_t m[3];
#pragma unroll
  for (int i = 0; i < 3; i++) m[i] = max(__float_as_uint(nr[2 * i]) & 0x7FFFFFFFu, __float_as_uint(nr[2 * i + 1]) & 0x7FFFFFFFu);
#pragma unroll
  for (int o = 4; o < 32; o <<= 1)
#pragma unroll
    for (int i = 0; i < 3; i++) m[i] = max(m[i], __shfl_xor_sync(0xffffffffu, m[i], o));
  if (r8 < 3) g_nrm[(ct * 12 + q4 * 3 + r8) * 128 + rb * 8 + warp] = __uint_as_float(r8 == 0 ? m[0] : r8 == 1 ? m[1] : m[2]);
  TS(1, 5);
}

__device__ __forceinline__ uint32_t exp2_pair_sw(float x0, float x1, uint32_t cm, uint32_t co) {
  float y0 = x0 + (65536.f + 127.f - 205.f / 128.f);
  float y1 = x1 + (65536.f + 496.f - 205.f / 128.f);
  uint32_t w = __float_as_uint(y1) * 65536u + __float_as_uint(y0);
  uint32_t m;
  asm("lop3.b32 %0, %1, %2, %3, 0xEA;" : "=r"(m) : "r"(w), "r"(cm), "r"(co));
  uint32_t p = fma_bf16x2(m, m, 0x40034003u);
  return w - m + p;
}
__device__ __forceinline__ uint32_t exp2_pair_hw(float x0, float x1) { return pack_bf16(ex2f(x0), ex2f(x1)); }
#define HW_MASK 0x2492u
#define ATT_SMEM (176 * 1040 + 1024 + TSX)
__device__ __forceinline__ uint64_t desc2(uint32_t lo, uint32_t hi) { uint64_t d; asm("mov.b64 %0, {%1, %2};" : "=l"(d) : "r"(lo), "r"(hi)); return d; }

template <int N> __device__ __forceinline__ void desc_add(uint64_t& d) {
  asm("{.reg .b32 lo, hi; mov.b64 {lo, hi}, %0; add.u32 lo, lo, %1; mov.b64 %0, {lo, hi};}" : "+l"(d) : "n"(N));
}
__device__ __forceinline__ void attn_store(float (&O)[12], bf16* op) {
  float r0 = 1.f / O[8], r1 = 1.f / O[10];
  *(uint32_t*)(op) = pack_bf16(O[0] * r0, O[1] * r0);
  *(uint32_t*)(op + 64) = pack_bf16(O[2] * r1, O[3] * r1);
  *(uint32_t*)(op + 512) = pack_bf16(O[4] * r0, O[5] * r0);
  *(uint32_t*)(op + 512 + 64) = pack_bf16(O[6] * r1, O[7] * r1);
}
struct AttOff { uint32_t k[2], v[8]; };
__device__ __forceinline__ void attn_fast(uint32_t sK, uint32_t sQ, uint32_t bar, bf16* op, bool first, const AttOff& off) {
  float S[32], O[12];
  uint32_t P0[16], P1[16];
#pragma unroll
  for (int i = 0; i < 12; i++) O[i] = 0.f;
#pragma unroll
  for (int i = 0; i < 32; i++) S[i] = 0.f;
  reg_fence(O); reg_fence(S);
  const uint32_t co = off.k[0] * (0x3F803F80u / 64);
  const uint64_t dQ = mk_desc(sQ, 8192, 128, 0);
  uint64_t dK[2], dV[8];
#pragma unroll
  for (int i = 0; i < 2; i++) dK[i] = mk_desc(sK, 32768, 128, 0) + off.k[i];
#pragma unroll
  for (int i = 0; i < 8; i++) dV[i] = mk_desc(sK + 65536, 128, 32768, 0) + off.v[i];
  wg_fence();
  wg_ss64(S, dQ, mk_desc(sK, 32768, 128, 0), 0);
  wg_commit();
  wg_commit();
  auto step = [&](uint32_t (&P)[16], int h, bool last) {
    wg_wait<1>();
    reg_fence(S);
#pragma unroll
    for (int j = 0; j < 16; j++) P[j] = (((HW_MASK) >> j) & 1) ? exp2_pair_hw(S[2 * j], S[2 * j + 1]) : exp2_pair_sw(S[2 * j], S[2 * j + 1], 0x007F007Fu, co);
    wg_fence();
    if (!last) {
      wg_ss64(S, dQ, dK[h], 0);
      desc_add<128>(dK[h]);
      wg_commit();
    }
#pragma unroll
    for (int kk = 0; kk < 4; kk++) { wg_rs24_t(O, P[4 * kk], P[4 * kk + 1], P[4 * kk + 2], P[4 * kk + 3], dV[h * 4 + kk], 1); desc_add<128>(dV[h * 4 + kk]); }
    wg_commit();
  };
#pragma unroll 1
  for (int c = 0; c < 4; c++) {
    if (first) mbar_wait(bar + 8 * c, 0);
#pragma unroll 1
    for (int i = c == 3; i < 4; i++) {
      step(P0, 0, false);
      step(P1, 1, false);
    }
  }
  step(P0, 0, false);
  step(P1, 1, true);
  wg_wait<0>();
  reg_fence(O);
  attn_store(O, op);
}
__device__ __forceinline__ void attn_safe(uint32_t sK, uint32_t sQ, uint32_t bar, bf16* op) {
  float S[32], O[12];
  uint32_t P[16];
#pragma unroll
  for (int i = 0; i < 12; i++) O[i] = 0.f;
#pragma unroll
  for (int i = 0; i < 32; i++) S[i] = 0.f;
  float m0 = -INFINITY, m1 = -INFINITY;
  const uint64_t dQ = mk_desc(sQ, 8192, 128, 0), dK = mk_desc(sK, 32768, 128, 0), dV = mk_desc(sK + 65536, 128, 32768, 0);
#pragma unroll 1
  for (int i = 0; i < 32; i++) {
    mbar_wait(bar + 8 * (i >> 3), 0);
    reg_fence(S);
    wg_fence();
    wg_ss64(S, dQ, dK + i * 64, 0);
    wg_commit();
    wg_wait<0>();
    reg_fence(S);
    float a = m0, b = m1;
#pragma unroll
    for (int j = 0; j < 8; j++) { a = fmaxf(a, fmaxf(S[4 * j], S[4 * j + 1])); b = fmaxf(b, fmaxf(S[4 * j + 2], S[4 * j + 3])); }
    a = fmaxf(a, __shfl_xor_sync(0xffffffffu, a, 1)); b = fmaxf(b, __shfl_xor_sync(0xffffffffu, b, 1));
    a = fmaxf(a, __shfl_xor_sync(0xffffffffu, a, 2)); b = fmaxf(b, __shfl_xor_sync(0xffffffffu, b, 2));
    float f0 = m0 == a ? 1.f : ex2f(m0 - a), f1 = m1 == b ? 1.f : ex2f(m1 - b);
    m0 = a; m1 = b;
#pragma unroll
    for (int j = 0; j < 3; j++) { O[4 * j] *= f0; O[4 * j + 1] *= f0; O[4 * j + 2] *= f1; O[4 * j + 3] *= f1; }
#pragma unroll
    for (int j = 0; j < 8; j++) { P[2 * j] = exp2_pair_hw(S[4 * j] - a, S[4 * j + 1] - a); P[2 * j + 1] = exp2_pair_hw(S[4 * j + 2] - b, S[4 * j + 3] - b); }
    reg_fence(O);
    wg_fence();
#pragma unroll
    for (int kk = 0; kk < 4; kk++) wg_rs24_t(O, P[4 * kk], P[4 * kk + 1], P[4 * kk + 2], P[4 * kk + 3], dV + i * 64 + kk * 16, 1);
    wg_commit();
    wg_wait<0>();
    reg_fence(O);
  }
  attn_store(O, op);
}

__device__ __forceinline__ void side_job(uint32_t sm, uint32_t sMod, const bf16* __restrict__ c, const bf16* __restrict__ wmod, const bf16* __restrict__ w_in) {
  const int t = threadIdx.x, j = blockIdx.x;
  sts32(sm + t * 4, __float_as_uint(silu_bf(c[t])));
  __syncthreads();
  float acc[8];
#pragma unroll
  for (int i = 0; i < 8; i++) acc[i] = 0.f;
  const int grp = (t & 63) >> 4, col = 1024 + grp * 512 + j * 128 + (t & 15) * 8;
  const bf16* wp = wmod + (size_t)(t >> 6) * 64 * 3072 + col;
#pragma unroll 16
  for (int k = 0; k < 64; k++) {
    const uint4 w = ldg128(wp + k * 3072);
    const float s = __uint_as_float(lds32(sm + ((t >> 6) * 64 + k) * 4));
    const uint32_t* q = (const uint32_t*)&w;
#pragma unroll
    for (int i = 0; i < 4; i++) { acc[2 * i] = fmaf(s, bf_lo(q[i]), acc[2 * i]); acc[2 * i + 1] = fmaf(s, bf_hi(q[i]), acc[2 * i + 1]); }
  }
#pragma unroll
  for (int i = 0; i < 8; i++) sts32(sm + 2048 + (t >> 6) * 2048 + (i * 64 + (t & 63)) * 4, __float_as_uint(acc[i]));
  __syncthreads();
  float v = 0.f;
#pragma unroll
  for (int i = 0; i < 8; i++) v += __uint_as_float(lds32(sm + 2048 + i * 2048 + t * 4));
  v = __bfloat162float(__float2bfloat16(v));
  const bf16 vb = __float2bfloat16(grp == 2 ? v + 1.f : v);
  g_mod[col + (t >> 6)] = vb;
  if (grp == 1 || grp == 2) sts32(sMod + ((t & 15) * 8 + (t >> 6)) * 8 + (grp & 1) * 4, __float_as_uint(__bfloat162float(vb)));
  const int kh = t >= 176, ch = t - kh * 176;
  float v1[8], v2[8];
#pragma unroll
  for (int i = 0; i < 8; i++) v1[i] = v2[i] = 0.f;
  for (int kb = 0; kb < 2; kb++) {
    __syncthreads();
    if (t < 352) {
#pragma unroll 16
      for (int k = kh * 32; k < kh * 32 + 32; k++) {
        uint4 w = ch < 172 ? ldg128(w_in + (size_t)(j * 128 + kb * 64 + k) * (2 * FH) + ch * 8) : make_uint4(0, 0, 0, 0);
        const float cc = __uint_as_float(lds32(sMod + (kb * 64 + k) * 8)), sb = __uint_as_float(lds32(sMod + (kb * 64 + k) * 8 + 4));
        uint32_t* q = (uint32_t*)&w;
#pragma unroll
        for (int i = 0; i < 4; i++) {
          v2[2 * i] = fmaf(sb, bf_lo(q[i]), v2[2 * i]); v2[2 * i + 1] = fmaf(sb, bf_hi(q[i]), v2[2 * i + 1]);
          q[i] = pack_bf16(cc * bf_lo(q[i]), cc * bf_hi(q[i]));
          v1[2 * i] += bf_lo(q[i]); v1[2 * i + 1] += bf_hi(q[i]);
        }
        sts128(sm + ch * 1040 + k * 16, w);
      }
    }
    fence_async_smem();
    __syncthreads();
    if (t < 176) {
      const int h = t >= 88, f = t - h * 88, ct = f / 11;
      bulk_s2g(g_win + (((ct * 2 + h) * 8 + 2 * j + kb) * 11 + f - ct * 11) * 512, sm + (f < 86 ? f + (h ? 0 : 86) : 172) * 1040, 1024);
      bulk_commit_wait();
    }
  }
  __syncthreads();
  if (kh && t < 352)
#pragma unroll
    for (int i = 0; i < 8; i++) { sts32(sm + (i * 352 + ch) * 4, __float_as_uint(v1[i])); sts32(sm + (i * 352 + t) * 4, __float_as_uint(v2[i])); }
  __syncthreads();
  if (t < 176) {
    float2* d = (float2*)g_v + j * 1408 + (t < 86 ? t : t < 172 ? t + 2 : t < 174 ? t - 86 : t) * 8;
#pragma unroll
    for (int i = 0; i < 8; i++) d[i] = make_float2(v1[i] + __uint_as_float(lds32(sm + (i * 352 + t) * 4)), v2[i] + __uint_as_float(lds32(sm + (i * 352 + 176 + t) * 4)));
  }
}

__global__ void __launch_bounds__(512, 1) k_attn(const bf16* __restrict__ c, const bf16* __restrict__ wmod, const bf16* __restrict__ w_in, const bf16* __restrict__ w_sp, const bf16* __restrict__ w_out, const bf16* __restrict__ wo, const __grid_constant__ AttOff off) {
  TS(2, 0);
  extern __shared__ uint8_t smem_raw[];
  __shared__ __align__(8) uint64_t bars[4];
  __shared__ __align__(16) uint32_t s_nrm[288];
  const uint32_t sK = (smem_u32(smem_raw) + 1023) & ~1023u, sQ = sK + 65536 + 98304;
  const uint32_t bar = smem_u32(bars);
  const int t = threadIdx.x, warp = __shfl_sync(0xffffffffu, t >> 5, 0), lane = t & 31;
  if (blockIdx.x < 4) { pdl_launch(); side_job(sK, smem_u32(s_nrm), c, wmod, w_in); TS(2, 5); return; }
  const int bid = blockIdx.x - 4, head = bid >> 2, quarter = bid & 3;
  if (t == 0) {
    for (int i = 0; i < 4; i++) mbar_init(bar + 8 * i, 1);
    fence_mbar_init();
    for (int i = 0; i < 4; i++) mbar_expect(bar + 8 * i, i == 0 ? 49152 + 1152 + 2048 : i == 3 ? 32768 - 2048 : 32768);
  }
#pragma unroll
  for (int i = 0; i < 4; i++) sts128(sK + 131072 + i * 8192 + t * 16, make_uint4(0x3F803F80u, 0x3F803F80u, 0x3F803F80u, 0x3F803F80u));
  if (t < 128) *(uint4*)(g_st + bid * 256 + t * 2) = make_uint4(~0u, ~0u, ~0u, ~0u);
  else if (t < 134) g_flag[bid * 6 + t - 128] = 0;
  fence_async_smem();
  __syncthreads();
  TS(2, 1);
  pdl_wait();
  pdl_launch();
  TS(2, 2);
  auto kv = [&](int c, int pl) {
    const int o = c * 8192 + (pl < 2 && c ? 1024 : 0), e = c * 8192 + 8192 + (pl < 2 && c < 3 ? 1024 : 0);
    bulk_g2s(sK + pl * 32768 + o, g_qkv + ((32 + (pl >> 1) * 32 + head) * 2 + (pl & 1)) * (SEQ * 8) + o / 2, e - o, bar + 8 * c);
  };
  if (lane == 0) {
    if (warp < 4) kv(0, warp);
    else if (warp < 6) bulk_g2s(sQ + (warp & 1) * 8192, g_qkv + (head * 2 + (warp & 1)) * (SEQ * 8) + quarter * 4096, 8192, bar);
    else if (warp < 8) bulk_g2s(smem_u32(s_nrm) + (warp & 1) * 512, g_nrm + (32 + (warp & 1) * 32 + head) * 128, 512, bar);
    else if (warp == 8) bulk_g2s(smem_u32(s_nrm) + 1024, g_nrm + head * 128 + quarter * 32, 128, bar);
  }
  __syncwarp();
  mbar_wait(bar, 0);
  if (lane == 0 && warp < 12) kv(1 + (warp >> 2), warp & 3);
  __syncwarp();
  if (t == 128) {
    int l = bid;
    if (l < 32) prefetch_l2(wo + l * 8192, 16384);
    else if (l < 75) prefetch_l2(w_out + (l - 32) * 8192, 16384);
    for (int i = 0; i < 4; i++) prefetch_l2(w_sp + (size_t)(l * 4 + i) * 8192, 16384);
  }
  if (t >= 256 && t < 304) *(uint4*)(g_mbx + bid * 192 + (t - 256) * 4) = make_uint4(0, 0, 0, 0);
  const uint4 nk = *(const uint4*)(s_nrm + lane * 4), nv = *(const uint4*)(s_nrm + 128 + lane * 4);
  const float mk = __uint_as_float(__reduce_max_sync(0xffffffffu, max(max(nk.x, nk.y), max(nk.z, nk.w))));
  const float mv = __uint_as_float(__reduce_max_sync(0xffffffffu, max(max(nv.x, nv.y), max(nv.z, nv.w))));
  const float mq = __uint_as_float(__reduce_max_sync(0xffffffffu, s_nrm[256 + lane]));
  const bool fast = (mq * mk <= 3900.f) && (mv <= 1e24f);
  const int wg = __shfl_sync(0xffffffffu, warp >> 2, 0);
  TS(2, 3); TSC(2, 0);
#pragma unroll 1
  for (int mt = 0; mt < 2; mt++) {
    const int rb64 = quarter * 8 + wg * 2 + mt, r = (warp & 3) * 16 + (lane >> 2);
    bf16* op = g_o + (rb64 * 64 + head * 2) * 512 + r * 8 + (lane & 3) * 2;
    const uint32_t sq = sQ + (wg * 2 + mt) * 1024;
    if (fast) attn_fast(sK, sq, bar, op, mt == 0, off);
    else attn_safe(sK, sq, bar, op);
  }
  TS(2, 5); TSC(2, 1);
}

#define POST_SMEM (131072 + 90112 + 1408 + 512 + TSX)
template <int N> __device__ __forceinline__ void put_tile(bf16* d, const uint32_t (&p)[N]) {
#pragma unroll
  for (int j = 0; j < N / 2; j++) { *(uint32_t*)(d + j * 512) = p[2 * j]; *(uint32_t*)(d + j * 512 + 64) = p[2 * j + 1]; }
}
template <int N> __device__ __forceinline__ void widen(float (&f)[2 * N], const uint32_t (&p)[N]) {
#pragma unroll
  for (int j = 0; j < N; j++) { f[2 * j] = bf_lo(p[j]); f[2 * j + 1] = bf_hi(p[j]); }
  reg_fence(f);
}
__device__ __forceinline__ void gate_add(uint32_t (&r)[16], const float (&x)[32], const float (&g)[16], const float (&a)[32]) {
#pragma unroll
  for (int j = 0; j < 16; j++) r[j] = pack_bf16(fmaf(g[j & ~1], a[2 * j], x[2 * j]), fmaf(g[j | 1], a[2 * j + 1], x[2 * j + 1]));
}
__device__ __forceinline__ void publish(uint32_t* flag) {
  asm volatile("red.release.gpu.global.add.u32 [%0], 1;" ::"l"(flag) : "memory");
}
__device__ __forceinline__ void flag_wait(const uint32_t* p, uint32_t n, uint32_t need, uint32_t& ready) {
  if ((ready & need) == need) return;
#pragma unroll 1
  for (int it = 0; it < SPIN_LIMIT; it++) {
    uint32_t v;
    asm volatile("ld.acquire.gpu.global.b32 %0, [%1];" : "=r"(v) : "l"(p) : "memory");
    ready = __ballot_sync(0xffffffffu, v == n);
    if ((ready & need) == need) { asm volatile("fence.proxy.async.global;" ::: "memory"); return; }
  }
  __trap();
}
__device__ __forceinline__ int sm_role() {
  uint32_t s; asm("mov.u32 %0, %%smid;" : "=r"(s));
  int g, l;
  if (s < 64) { g = (s >> 1) & 7; l = (s >> 4) * 2 + (s & 1); }
  else if (s < 120) { const int q = (s - 64) >> 1; g = 1 + q % 7; l = 8 + q / 7 * 2 + (s & 1); }
  else { g = 0; l = s - 112; }
  if ((g & 1) && g != 3 && g != 5) g = 8 - g;
  return s < 128 ? ((g >> 1) * 4 + (l >> 2)) * 8 + (g & 1) * 4 + (l & 3) : -1;
}
__global__ void __launch_bounds__(384, 1)
k_post(const bf16* __restrict__ x, const bf16* __restrict__ b_sp, const __grid_constant__ CUtensorMap tmWo, const __grid_constant__ CUtensorMap tmS,
       const __grid_constant__ CUtensorMap tmWout, const __grid_constant__ CUtensorMap tmOut) {
  TS(3, 0);
  extern __shared__ __align__(1024) uint8_t smem_raw[];
  const uint32_t sA = smem_u32(smem_raw), sB = sA + 131072, sV = sB + 90112;
  const uint32_t full = sV + 1408, empty = full + 64, fullB = empty + 64, emptyB = fullB + 64, fullU = emptyB + 64;
  const int t = threadIdx.x, warp = __shfl_sync(0xffffffffu, t >> 5, 0), lane = t & 31;
  int role = blockIdx.x;
  if (gridDim.x == 132) {
    role = sm_role();
    if (t == 0) asm volatile("red.relaxed.gpu.global.add.u32 [%0], 1;" ::"l"(g_cnt) : "memory");
    if (role < 0) {
      if (t == 0) for (int it = 0; mbx_ld(g_cnt) < 132u; it++) { if (it > SPIN_LIMIT) __trap(); __nanosleep(200); }
      return;
    }
  }
  const int rb = role >> 3, ct = role & 7;
  if (t == 256) {
    if (sA & 1023) __trap();
    for (int i = 0; i < 8; i++) { mbar_init(full + 8 * i, 1); mbar_init(empty + 8 * i, 2); mbar_init(fullB + 8 * i, 1); mbar_init(emptyB + 8 * i, 2); }
    for (int i = 0; i < 11; i++) mbar_init(fullU + 8 * i, 1);
    fence_mbar_init();
    for (int i = 0; i < 8; i++) mbar_expect(full + 8 * i, i & 3 ? 8192 : 8192 + 65536);
    for (int i = 0; i < 4; i++) tma_2d(sA + (i & 1) * 65536 + (i >> 1) * 32768, &tmWo, (ct & 3) * 128 + (i & 1) * 64, (i >> 1) * 256, full + (i >> 1) * 32);
    for (int i = 0; i < 11; i++) mbar_expect(fullU + 8 * i, 8192);
    prefetch_tmap(&tmS); prefetch_tmap(&tmWout); prefetch_tmap(&tmOut);
  }
  const int wg = warp >> 2, q4 = lane & 3;
  const int row = rb * 128 + warp * 16 + (lane >> 2);
  const int ho = rb * 2 + (ct >> 2), co = (ct & 3) * 2 + wg;
  const int rowo = ho * 64 + (warp & 3) * 16 + (lane >> 2), col0 = co * 64 + q4 * 2;
  uint32_t xr[16];
  if (warp < 8) {
#pragma unroll
    for (int j = 0; j < 8; j++) {
      xr[2 * j] = __ldg((const uint32_t*)(x + (size_t)rowo * DM + col0 + j * 8));
      xr[2 * j + 1] = __ldg((const uint32_t*)(x + (size_t)(rowo + 8) * DM + col0 + j * 8));
    }
  }
  __syncthreads();
  TS(3, 1);
  pdl_wait();
  TS(3, 2);
  if (warp >= 8) {
    const int p = warp - 8, hb = rb * 2 + (p & 1);
    auto loadA = [&](const bf16* src, int stride, int s) {
      bulk_g2s(sA + s * 16384, src, 8192, full + 8 * s); bulk_g2s(sA + s * 16384 + 8192, src + stride, 8192, full + 8 * s);
    };
    auto loadW = [&](int kb) {
      mbar_expect(fullB + 8 * (kb & 7), 11264);
      bulk_g2s(sB + (kb & 7) * 11264, g_win + (ct * 16 + kb) * 5632, 11264, fullB + 8 * (kb & 7));
    };
    if (lane == 0) {
      for (int kb = p; kb < 8; kb += 4) bulk_g2s(sB + (kb + 3) * 8192, g_o + ho * 32768 + kb * 4096, 8192, full + 8 * kb);
      const int q = p ^ 2;
      if (q >= 2) mbar_wait(empty + 8 * q - 8, 0);
      loadW(q);
      mbar_wait(empty + 8 * (q ? q + 4 : 3), 0);
      loadW(q + 4);
      mbar_wait(empty + 56, 0);
      mbar_expect(full + 8 * p, 16384); mbar_expect(full + 8 * p + 32, 16384);
    }
    __syncwarp();
    if (p >= 2) {
      bar_sync(p - 1, 160);
      if (lane == 0) { publish(g_flag + rb * 8 + (ct & 3) * 2 + (p & 1)); if (p == 2) TSA(24); }
      __syncwarp();
    }
    uint32_t ready = 0;
    for (int kb = p; kb < 8; kb += 4) {
      flag_wait(g_flag + rb * 8 + (lane & 7), 2, 1u << kb, ready);
      if (lane == 0) loadA(g_x1 + rb * 65536 + kb * 4096, 32768, kb);
      if (kb == 0) TSA(25);
      if (kb == 7) TSA(26);
    }
    const int rot = (rb >> 2) * 8;
    auto loadS = [&](int i) {
      const int s = i & 7;
      mbar_wait(empty + 8 * s, ((i >> 3) + 1) & 1);
      mbar_expect(full + 8 * s, 16384 + 11264);
      tma_2d(sA + s * 16384, &tmS, ((i + rot) & 31) * 64, rb * 128, full + 8 * s);
    };
    if (lane == 0) { mbar_wait(emptyB + 8 * p, 0); loadW(8 + p); mbar_wait(emptyB + 8 * p + 32, 0); loadW(12 + p); }
    if (lane == 0) loadS(p);
    __syncwarp();
    if (p >= 2) bar_sync(p - 1, 160);
    if (lane == 0) {
      if (p >= 2) publish(g_flag + 256 + ((ct >> 2) * 4 + (rb >> 2)) * 32);
      if (p == 2) TSA(27);
    }
    __syncwarp();
    ready = 0;
    const bf16* zp = g_z2 + ct * 32 * 5632;
    for (int i = p; i < 32; i += 4) {
      flag_wait(g_flag + 256 + ((ct >> 2) * 4 + (lane & 3)) * 32, 32, i < 8 ? 1u << (rb >> 2) : 15u, ready);
      if (lane == 0) {
        if (i >= 4) loadS(i);
        bulk_g2s(sB + (i & 7) * 11264, zp + ((i + rot) & 31) * 5632, 11264, full + 8 * (i & 7));
        if (i == 0) TSA(28);
        if (i == 7) TSA(29);
      }
    }
    auto loadF = [&](int j) {
      const int s = j & 7;
      mbar_wait(empty + 8 * s, j < 8);
      mbar_expect(full + 8 * s, 16384);
      for (int w = 0; w < 2; w++) tma_2d(sA + s * 16384 + w * 8192, &tmWout, (ct & 3) * 128 + w * 64, j * 64, full + 8 * s);
    };
    if (lane == 0) { loadF(p); loadF(p + 4); mbar_wait(empty + 56, 1); }
    __syncwarp();
    if (p >= 2) {
      bar_sync(p - 1, 160);
      if (lane == 0) {
        publish(g_flag + 512 + hb * 8 + ct);
        if (p == 2) TSA(30);
      }
      __syncwarp();
    }
    ready = 0;
    for (int j = p; j < 11; j += 4) {
      flag_wait(g_flag + 512 + ho * 8 + (lane & 7), 1, (1u << (j * 8 / 11)) | (1u << ((j * 8 + 7) / 11)), ready);
      if (lane == 0) {
        bulk_g2s(sB + j * 8192, g_u + ho * (88 * 512) + j * 4096, 8192, fullU + 8 * j);
        if (j >= 8) loadF(j);
        if (j == 0) TSA(31);
        if (j == 7) TSA(19);
      }
    }
  } else {
    const uint64_t dA0 = mk_desc(sA + wg * 8192, 1024, 128, 0), dAh = mk_desc(sB, 1024, 128, 0), dB64 = mk_desc(sA, 8192, 1024, 1), dB88 = mk_desc(sB, 128, 1024, 0);
    const bool rel = (t & 127) == 0;
    const int hb = rb * 2 + wg, tp = (warp & 3) * 128 + lane * 2;
    {
      uint32_t ga[8];
#pragma unroll
      for (int j = 0; j < 8; j++) ga[j] = *(const uint32_t*)(g_mod + 1024 + col0 + j * 8);
      float2 va, vb, vd, ve;
      if (t < 176) {
        const int h = t >= 88, c = t - h * 88;
        const float* p = g_v + (ct * 88 + c + (h ? 0 : 704)) * 2;
        va = *(const float2*)p; vb = *(const float2*)(p + 2816); vd = *(const float2*)(p + 5632); ve = *(const float2*)(p + 8448);
      }
      float acc[32];
#pragma unroll 1
      for (int kb = 0; kb < 8; kb++) {
        mbar_wait(full + 8 * kb, 0);
        if (kb == 0) TS(9, 6);
        if (kb == 7) TS(9, 7);
        wg_fence();
#pragma unroll
        for (int kk = 0; kk < 4; kk++) wg_ss64_t(acc, dAh + (kb + 3) * 512 + kk * 128, dB64 + wg * 4096 + kb * 512 + kk * 128, (kb | kk) != 0);
        wg_commit();
        if (kb) { wg_wait<1>(); if (rel) mbar_arrive(empty + 8 * kb - 8); }
      }
      float xf[32], gf[16];
      widen(xf, xr); widen(gf, ga);
      wg_wait<0>();
      reg_fence(acc);
      TS(3, 3);
      if (rel) mbar_arrive(empty + 56);
      gate_add(xr, xf, gf, acc);
      put_tile(g_x1 + (ho * 64 + co * 8) * 512 + tp, xr);
      bar_arrive(1 + wg, 160);
#pragma unroll
      for (int j = 0; j < 16; j++) asm volatile("" : "+r"(xr[j]));
      widen(acc, xr);
      float s0 = 0.f, s1 = 0.f;
#pragma unroll
      for (int j = 0; j < 8; j++) { s0 += acc[4 * j] + acc[4 * j + 1]; s1 += acc[4 * j + 2] + acc[4 * j + 3]; }
      s0 += __shfl_xor_sync(0xffffffffu, s0, 1); s1 += __shfl_xor_sync(0xffffffffu, s1, 1);
      s0 += __shfl_xor_sync(0xffffffffu, s0, 2); s1 += __shfl_xor_sync(0xffffffffu, s1, 2);
      s0 *= (1.f / 64); s1 *= (1.f / 64);
      float q0 = 0.f, q1 = 0.f;
#pragma unroll
      for (int j = 0; j < 8; j++) {
        float a = acc[4 * j] - s0, b = acc[4 * j + 1] - s0, c = acc[4 * j + 2] - s1, d = acc[4 * j + 3] - s1;
        q0 = fmaf(a, a, fmaf(b, b, q0)); q1 = fmaf(c, c, fmaf(d, d, q1));
      }
      q0 += __shfl_xor_sync(0xffffffffu, q0, 1); q1 += __shfl_xor_sync(0xffffffffu, q1, 1);
      q0 += __shfl_xor_sync(0xffffffffu, q0, 2); q1 += __shfl_xor_sync(0xffffffffu, q1, 2);
      if (q4 < 2) stat_put(g_st + (rowo + 8 * q4) * 8 + co, q4 ? s1 : s0, q4 ? q1 : q0);
      if (t < 176) {
        const uint32_t o = sV + (t >> 1) * 16 + (t & 1) * 4;
        sts32(o, __float_as_uint((va.x + vb.x) + (vd.x + ve.x))); sts32(o + 8, __float_as_uint((va.y + vb.y) + (vd.y + ve.y)));
      }
      bar_sync(3, 256);
    }
    TS(3, 4);
    float acc[44], ac1[44];
#pragma unroll 1
    for (int kb = 0; kb < 8; kb++) {
      mbar_wait2(full + 8 * kb, 1, fullB + 8 * kb);
      if (kb == 0) TS(8, 0);
      wg_fence();
#pragma unroll
      for (int kk = 0; kk < 4; kk++) wg_ss88_t(acc, dA0 + kb * 1024 + kk * 128, dB88 + kb * 704 + kk * 16, (kb | kk) != 0);
      wg_commit();
      if (kb == 6) { wg_wait<1>(); if ((t & 127) < 6) mbar_arrive(emptyB + 8 * lane); }
    }
    float rs[2], mr[2];
    stat_get(g_st + row * 8 + q4 * 2, 64.f, 64.f, 1.f / DM, rs, mr);
    auto pass2 = [&](int k0) {
#pragma unroll 1
      for (int kb = k0; kb < k0 + 4; kb++) {
        mbar_wait(fullB + 8 * kb, 1);
        wg_fence();
#pragma unroll
        for (int kk = 0; kk < 4; kk++) wg_ss88_t(ac1, dA0 + kb * 1024 + kk * 128, dB88 + kb * 704 + kk * 16, (kb | kk) != 0);
      }
      wg_commit();
    };
    wg_wait<0>();
    reg_fence(acc);
    if ((t & 127) < 2) mbar_arrive(emptyB + 48 + 8 * lane);
    TS(8, 1);
    const int nch = ct == 7 ? 9 : 11;
    auto act = [&](float (&a)[44], uint32_t v) {
#pragma unroll
      for (int j = 0; j < 11; j++) {
        const uint4 c = lds128(v + j * 64);
        a[4 * j] = gelu_tanh(fmaf(a[4 * j], rs[0], fmaf(mr[0], __uint_as_float(c.x), __uint_as_float(c.z))));
        a[4 * j + 1] = gelu_tanh(fmaf(a[4 * j + 1], rs[0], fmaf(mr[0], __uint_as_float(c.y), __uint_as_float(c.w))));
        a[4 * j + 2] = gelu_tanh(fmaf(a[4 * j + 2], rs[1], fmaf(mr[1], __uint_as_float(c.x), __uint_as_float(c.z))));
        a[4 * j + 3] = gelu_tanh(fmaf(a[4 * j + 3], rs[1], fmaf(mr[1], __uint_as_float(c.y), __uint_as_float(c.w))));
      }
    };
    act(acc, sV + q4 * 16);
    {
      float s0 = 0.f, s1 = 0.f;
#pragma unroll
      for (int j = 0; j < 11; j++) { s0 += acc[4 * j] + acc[4 * j + 1]; s1 += acc[4 * j + 2] + acc[4 * j + 3]; }
      s0 += __shfl_xor_sync(0xffffffffu, s0, 1); s1 += __shfl_xor_sync(0xffffffffu, s1, 1);
      s0 += __shfl_xor_sync(0xffffffffu, s0, 2); s1 += __shfl_xor_sync(0xffffffffu, s1, 2);
      const float ic = ct == 7 ? 1.f / 72 : 1.f / 88;
      s0 *= ic; s1 *= ic;
      float q0 = 0.f, q1 = 0.f;
#pragma unroll
      for (int j = 0; j < 11; j++) {
        if (j < nch) {
          float a = acc[4 * j] - s0, b = acc[4 * j + 1] - s0, c = acc[4 * j + 2] - s1, d = acc[4 * j + 3] - s1;
          q0 = fmaf(a, a, fmaf(b, b, q0)); q1 = fmaf(c, c, fmaf(d, d, q1));
        }
      }
      q0 += __shfl_xor_sync(0xffffffffu, q0, 1); q1 += __shfl_xor_sync(0xffffffffu, q1, 1);
      q0 += __shfl_xor_sync(0xffffffffu, q0, 2); q1 += __shfl_xor_sync(0xffffffffu, q1, 2);
      if (q4 < 2) stat_put(g_st + 8 * SEQ + (row + 8 * q4) * 8 + ct, q4 ? s1 : s0, q4 ? q1 : q0);
    }
    TS(8, 2);
    pass2(0);
    uint32_t pk[22];
    {
      float r2[2], m2[2];
      stat_get(g_st + 8 * SEQ + row * 8 + q4 * 2, 88.f, q4 == 3 ? 72.f : 88.f, 1.f / FH, r2, m2);
      wg_wait<0>();
      if ((t & 127) < 4) mbar_arrive(empty + lane * 8);
      TS(8, 3);
#pragma unroll
      for (int j = 0; j < 11; j++) {
        pk[2 * j] = j < nch ? pack_bf16(fmaf(acc[4 * j], r2[0], m2[0]), fmaf(acc[4 * j + 1], r2[0], m2[0])) : 0u;
        pk[2 * j + 1] = j < nch ? pack_bf16(fmaf(acc[4 * j + 2], r2[1], m2[1]), fmaf(acc[4 * j + 3], r2[1], m2[1])) : 0u;
      }
    }
    put_tile(g_z2 + (ct * 32 + hb) * 5632 + tp, pk);
    bar_arrive(1 + wg, 160);
    TS(8, 4);
    pass2(4);
    wg_wait<0>();
    reg_fence(ac1);
    if ((t & 127) < 4) mbar_arrive(empty + lane * 8 + 32);
    const float b0 = __bfloat162float(b_sp[row]), b1 = __bfloat162float(b_sp[row + 8]);
    act(ac1, sV + 704 + q4 * 16);
#pragma unroll
    for (int j = 0; j < 22; j++) { pk[j] = pack_bf16(ac1[2 * j], ac1[2 * j + 1]); acc[2 * j] = acc[2 * j + 1] = j & 1 ? b1 : b0; }
    widen(ac1, pk);
    reg_fence(acc);
    TS(8, 5);
    const uint64_t dAs = mk_desc(sA + wg * 8192, 16, 1024, 1);
#pragma unroll 1
    for (int i = 0; i < 32; i++) {
      const int s = i & 7;
      mbar_wait(full + 8 * s, (i >> 3) & 1);
      if (i == 0) TS(8, 6);
      wg_fence();
#pragma unroll
      for (int kk = 0; kk < 4; kk++) wg_ss88_t(acc, dAs + s * 1024 + kk * 2, dB88 + s * 704 + kk * 16, 1);
      wg_commit();
      if (i) { wg_wait<1>(); if (rel) mbar_arrive(empty + ((i - 1) & 7) * 8); }
    }
    wg_wait<0>();
    reg_fence(acc);
    if (rel) mbar_arrive(empty + 56);
    TS(8, 7);
#pragma unroll
    for (int j = 0; j < 22; j++) pk[j] = pack_bf16(acc[2 * j] * ac1[2 * j], acc[2 * j + 1] * ac1[2 * j + 1]);
    put_tile(g_u + (hb * 88 + ct * 11) * 512 + tp, pk);
    bar_arrive(1 + wg, 160);
    TS(9, 0);
    uint32_t gb[8];
#pragma unroll
    for (int j = 0; j < 8; j++) gb[j] = *(const uint32_t*)(g_mod + 2560 + col0 + j * 8);
    float (&ac)[32] = *(float(*)[32])ac1;
    float xf[32], gf[16];
    widen(xf, xr); widen(gf, gb);
#pragma unroll 1
    for (int j = 0; j < 11; j++) {
      const int s = j & 7;
      mbar_wait2(full + 8 * s, j >> 3, fullU + 8 * j);
      if (j == 0) TS(9, 1);
      wg_fence();
#pragma unroll
      for (int kk = 0; kk < 4; kk++) wg_ss64_t(ac, dAh + j * 512 + kk * 128, dB64 + s * 1024 + wg * 512 + kk * 128, (j | kk) != 0);
      wg_commit();
      if (j >= 1 && j < 4) { wg_wait<1>(); if (rel) mbar_arrive(empty + (j - 1) * 8); }
    }
    wg_wait<0>();
    reg_fence(ac);
    TS(9, 2);
    gate_add(xr, xf, gf, ac);
#pragma unroll
    for (int j = 0; j < 8; j += 2)
      stsm4(sA + 49152 + warp * 2048 + (lane & 15) * 128 + (((j + (lane >> 4)) ^ (lane & 7)) << 4), xr[2 * j], xr[2 * j + 1], xr[2 * j + 2], xr[2 * j + 3]);
    fence_async_smem();
    __syncwarp();
    if (lane == 0) {
      asm volatile("cp.async.bulk.tensor.2d.global.shared::cta.bulk_group [%0, {%1, %2}], [%3];" ::"l"(&tmOut), "r"(co * 64), "r"(ho * 64 + (warp & 3) * 16), "r"(sA + 49152 + warp * 2048) : "memory");
      asm volatile("cp.async.bulk.commit_group;" ::: "memory");
      asm volatile("cp.async.bulk.wait_group.read 0;" ::: "memory");
    }
    TS(3, 5);
  }
}

typedef CUresult (*EncodeFn)(CUtensorMap*, CUtensorMapDataType, cuuint32_t, void*, const cuuint64_t*, const cuuint64_t*, const cuuint32_t*,
                             const cuuint32_t*, CUtensorMapInterleave, CUtensorMapSwizzle, CUtensorMapL2promotion, CUtensorMapFloatOOBfill);
static void make_map(EncodeFn fn, CUtensorMap* m, const void* p, uint64_t inner, uint64_t outer, uint32_t bi, uint32_t bo, CUtensorMapSwizzle sw = CU_TENSOR_MAP_SWIZZLE_128B) {
  cuuint64_t dims[2] = {inner, outer}, strides[1] = {inner * 2};
  cuuint32_t box[2] = {bi, bo}, es[2] = {1, 1};
  fn(m, CU_TENSOR_MAP_DATA_TYPE_BFLOAT16, 2, (void*)p, dims, strides, box, es, CU_TENSOR_MAP_INTERLEAVE_NONE, sw,
     CU_TENSOR_MAP_L2_PROMOTION_L2_256B, CU_TENSOR_MAP_FLOAT_OOB_FILL_NONE);
}
template <typename... KA, typename... A>
static void launch(void (*k)(KA...), int grid, int block, int smem, bool pdl, A... args) {
  cudaLaunchConfig_t cfg = {};
  cfg.gridDim = dim3(grid); cfg.blockDim = dim3(block); cfg.dynamicSmemBytes = smem; cfg.stream = cudaStreamPerThread;
  cudaLaunchAttribute at[1];
  at[0].id = cudaLaunchAttributeProgrammaticStreamSerialization; at[0].val.programmaticStreamSerializationAllowed = 1;
  cfg.attrs = at; cfg.numAttrs = pdl ? 1 : 0;
  cudaLaunchKernelEx(&cfg, k, args...);
}

extern "C" void kernel_launch(void* const* d_in, const int* in_sizes, int n_in, void* d_out, int out_size) {
  const bf16* x = (const bf16*)d_in[0]; const bf16* wqkv = (const bf16*)d_in[1]; const bf16* wo = (const bf16*)d_in[2];
  const bf16* w_in = (const bf16*)d_in[4]; const bf16* w_sp = (const bf16*)d_in[5]; const bf16* b_sp = (const bf16*)d_in[6];
  const bf16* w_out = (const bf16*)d_in[7]; const bf16* c = (const bf16*)d_in[8]; const bf16* w_mod = (const bf16*)d_in[9];
  static EncodeFn fn = nullptr;
  static int nsm = 0;
  if (!fn) {
    cudaDeviceGetAttribute(&nsm, cudaDevAttrMultiProcessorCount, 0);
    cudaDriverEntryPointQueryResult qr;
    cudaGetDriverEntryPoint("cuTensorMapEncodeTiled", (void**)&fn, cudaEnableDefault, &qr);
    cudaFuncSetAttribute(k_qkv, cudaFuncAttributeMaxDynamicSharedMemorySize, QKV_SMEM);
    cudaFuncSetAttribute(k_attn, cudaFuncAttributeMaxDynamicSharedMemorySize, ATT_SMEM);
    cudaFuncSetAttribute(k_post, cudaFuncAttributeMaxDynamicSharedMemorySize, POST_SMEM);
  }
  CUtensorMap mX, mQ, mO, mS, mW, mY;
  make_map(fn, &mX, x, 512, 2048, 64, 128);
  make_map(fn, &mQ, wqkv, 1536, 512, 64, 64);
  make_map(fn, &mO, wo, 512, 512, 64, 256);
  make_map(fn, &mS, w_sp, 2048, 2048, 64, 128);
  make_map(fn, &mY, d_out, 512, 2048, 64, 16);
  make_map(fn, &mW, w_out, 512, FH, 64, 64);
  launch(k_qkv, 128, 288, QKV_SMEM, false, x, c, w_mod, wqkv, mX, mQ);
  AttOff off;
  for (int i = 0; i < 2; i++) off.k[i] = 64 * (i + 1);
  for (int i = 0; i < 8; i++) off.v[i] = 16 * i;
  launch(k_attn, 132, 512, ATT_SMEM, true, c, w_mod, w_in, w_sp, w_out, wo, off);
  launch(k_post, nsm == 132 ? 132 : 128, 384, POST_SMEM, true, x, b_sp, mO, mS, mW, mY);
}
```

```cpp
#include <cuda_runtime.h>
#include <cuda_bf16.h>
#include <cuda.h>
#include <stdint.h>

typedef __nv_bfloat16 bf16;
#define SEQ 2048
#define DM 512
#define FH 688
#define SPIN_LIMIT (1 << 22)

__device__ __align__(128) bf16 g_mod[6 * DM];
__device__ __align__(128) uint32_t g_mbx[12 * SEQ];
__device__ __align__(128) bf16 g_win[8 * 2 * 8 * 11 * 512];
__device__ __align__(128) bf16 g_qkv[96 * 2 * SEQ * 8];
__device__ __align__(128) float g_nrm[96 * 128];
__device__ __align__(128) bf16 g_o[32 * 64 * 64 * 8];
__device__ __align__(128) bf16 g_x1[32 * 64 * 64 * 8];
__device__ __align__(128) float g_v[4 * 1408 * 2];
__device__ __align__(128) uint32_t g_flag[768];
__device__ __align__(128) uint32_t g_cnt[32];
__device__ __align__(128) bf16 g_z2[8 * 32 * 11 * 64 * 8];
__device__ __align__(128) uint2 g_st[2 * 8 * SEQ];
__device__ __align__(128) bf16 g_u[32 * 88 * 64 * 8];

#define TSX 0
#define TSL(i)
#define TSB
#define TSA(i)
#define TS(k, p)
#define TSC(k, p)
__device__ __forceinline__ uint32_t smem_u32(const void* p) { return (uint32_t)__cvta_generic_to_shared(p); }
__device__ __forceinline__ void mbar_init(uint32_t a, int c) { asm volatile("mbarrier.init.shared::cta.b64 [%0], %1;" ::"r"(a), "r"(c) : "memory"); }
__device__ __forceinline__ void mbar_expect(uint32_t a, uint32_t b) { asm volatile("mbarrier.arrive.expect_tx.shared::cta.b64 _, [%0], %1;" ::"r"(a), "r"(b) : "memory"); }
__device__ __forceinline__ void mbar_arrive(uint32_t a) { asm volatile("mbarrier.arrive.shared::cta.b64 _, [%0];" ::"r"(a) : "memory"); }
__device__ __forceinline__ void mbar_wait(uint32_t a, uint32_t ph) {
  uint32_t ok;
  asm volatile("{.reg .pred p; mbarrier.try_wait.parity.shared::cta.b64 p, [%1], %2; selp.u32 %0, 1, 0, p;}" : "=r"(ok) : "r"(a), "r"(ph) : "memory");
  if (ok) return;
#pragma unroll 1
  for (int it = 0; it < SPIN_LIMIT; it++) {
    asm volatile("{.reg .pred p; mbarrier.try_wait.parity.shared::cta.b64 p, [%1], %2; selp.u32 %0, 1, 0, p;}" : "=r"(ok) : "r"(a), "r"(ph) : "memory");
    if (ok) return;
  }
  __trap();
}
__device__ __forceinline__ void mbar_wait2(uint32_t a, uint32_t ph, uint32_t b) {
  uint32_t ok;
  asm volatile("{.reg .pred p, q; mbarrier.try_wait.parity.shared::cta.b64 p, [%1], %2; mbarrier.try_wait.parity.shared::cta.b64 q, [%3], 0; and.pred p, p, q; selp.u32 %0, 1, 0, p;}"
               : "=r"(ok) : "r"(a), "r"(ph), "r"(b) : "memory");
  if (ok) return;
  mbar_wait(a, ph); mbar_wait(b, 0);
}
__device__ __forceinline__ void fence_mbar_init() { asm volatile("fence.mbarrier_init.release.cluster;" ::: "memory"); }
__device__ __forceinline__ void fence_async_smem() { asm volatile("fence.proxy.async.shared::cta;" ::: "memory"); }
__device__ __forceinline__ void bulk_g2s(uint32_t dst, const void* src, uint32_t bytes, uint32_t bar) {
  asm volatile("cp.async.bulk.shared::cluster.global.mbarrier::complete_tx::bytes [%0], [%1], %2, [%3];" ::"r"(dst), "l"(src), "r"(bytes), "r"(bar) : "memory");
}
__device__ __forceinline__ void tma_2d(uint32_t dst, const CUtensorMap* tm, int c0, int c1, uint32_t bar) {
  asm volatile("cp.async.bulk.tensor.2d.shared::cluster.global.mbarrier::complete_tx::bytes [%0], [%1, {%3, %4}], [%2];" ::"r"(dst), "l"(tm), "r"(bar), "r"(c0), "r"(c1) : "memory");
}
__device__ __forceinline__ void prefetch_l2(const void* p, uint32_t bytes) { asm volatile("cp.async.bulk.prefetch.L2.global [%0], %1;" ::"l"(p), "r"(bytes) : "memory"); }
__device__ __forceinline__ void prefetch_tmap(const CUtensorMap* tm) { asm volatile("prefetch.tensormap [%0];" ::"l"(tm) : "memory"); }
__device__ __forceinline__ void pdl_wait() { asm volatile("griddepcontrol.wait;" ::: "memory"); }
__device__ __forceinline__ void pdl_launch() { asm volatile("griddepcontrol.launch_dependents;" ::: "memory"); }
__device__ __forceinline__ void wg_fence() { asm volatile("wgmma.fence.sync.aligned;" ::: "memory"); }
__device__ __forceinline__ void wg_commit() { asm volatile("wgmma.commit_group.sync.aligned;" ::: "memory"); }
template <int N> __device__ __forceinline__ void wg_wait() { asm volatile("wgmma.wait_group.sync.aligned %0;" ::"n"(N) : "memory"); }
template <int N> __device__ __forceinline__ void reg_fence(float (&d)[N]) {
#pragma unroll
  for (int i = 0; i < N; i++) asm volatile("" : "+f"(d[i])::"memory");
}
__device__ __forceinline__ void bar_sync(int id, int n) { asm volatile("bar.sync %0, %1;" ::"r"(id), "r"(n) : "memory"); }
__device__ __forceinline__ void bar_arrive(int id, int n) { asm volatile("bar.arrive %0, %1;" ::"r"(id), "r"(n) : "memory"); }
__device__ __forceinline__ uint64_t mk_desc(uint32_t addr, uint32_t lbo, uint32_t sbo, uint32_t swz) {
  return (uint64_t)((addr & 0x3FFFF) >> 4) | ((uint64_t)(lbo >> 4) << 16) | ((uint64_t)(sbo >> 4) << 32) | ((uint64_t)swz << 62);
}
__device__ __forceinline__ uint32_t pack_bf16(float lo, float hi) {
  uint32_t r; asm("cvt.rn.bf16x2.f32 %0, %1, %2;" : "=r"(r) : "f"(hi), "f"(lo)); return r;
}
__device__ __forceinline__ float bf_lo(uint32_t v) { return __uint_as_float(v << 16); }
__device__ __forceinline__ float bf_hi(uint32_t v) { return __uint_as_float(v & 0xFFFF0000u); }
__device__ __forceinline__ uint32_t fma_bf16x2(uint32_t a, uint32_t b, uint32_t c) {
  uint32_t r; asm("fma.rn.bf16x2 %0, %1, %2, %3;" : "=r"(r) : "r"(a), "r"(b), "r"(c)); return r;
}
__device__ __forceinline__ float ex2f(float x) { float r; asm("ex2.approx.ftz.f32 %0, %1;" : "=f"(r) : "f"(x)); return r; }
__device__ __forceinline__ float rcpf(float x) { float r; asm("rcp.approx.ftz.f32 %0, %1;" : "=f"(r) : "f"(x)); return r; }
__device__ __forceinline__ float tanhf_hw(float x) { float r; asm("tanh.approx.f32 %0, %1;" : "=f"(r) : "f"(x)); return r; }
__device__ __forceinline__ float gelu_tanh(float z) {
  float t = tanhf_hw(z * fmaf(z * z, 0.0356774081f, 0.7978845608f));
  float hz = 0.5f * z;
  return fmaf(hz, t, hz);
}
__device__ __forceinline__ uint4 ldg128(const void* p) { return __ldg((const uint4*)p); }
__device__ __forceinline__ void sts128(uint32_t a, uint4 v) { asm volatile("st.shared.v4.b32 [%0], {%1,%2,%3,%4};" ::"r"(a), "r"(v.x), "r"(v.y), "r"(v.z), "r"(v.w) : "memory"); }

__device__ __forceinline__ uint4 lds128(uint32_t a) { uint4 v; asm volatile("ld.shared.v4.b32 {%0,%1,%2,%3}, [%4];" : "=r"(v.x), "=r"(v.y), "=r"(v.z), "=r"(v.w) : "r"(a) : "memory"); return v; }
__device__ __forceinline__ void sts32(uint32_t a, uint32_t v) { asm volatile("st.shared.b32 [%0], %1;" ::"r"(a), "r"(v) : "memory"); }
__device__ __forceinline__ uint32_t lds32(uint32_t a) { uint32_t v; asm volatile("ld.shared.b32 %0, [%1];" : "=r"(v) : "r"(a) : "memory"); return v; }
__device__ __forceinline__ void ldsm4(uint32_t* r, uint32_t a) {
  asm volatile("ldmatrix.sync.aligned.m8n8.x4.shared.b16 {%0,%1,%2,%3}, [%4];" : "=r"(r[0]), "=r"(r[1]), "=r"(r[2]), "=r"(r[3]) : "r"(a) : "memory");
}
__device__ __forceinline__ void stsm4(uint32_t a, uint32_t r0, uint32_t r1, uint32_t r2, uint32_t r3) {
  asm volatile("stmatrix.sync.aligned.m8n8.x4.shared.b16 [%0], {%1,%2,%3,%4};" ::"r"(a), "r"(r0), "r"(r1), "r"(r2), "r"(r3) : "memory");
}
__device__ __forceinline__ void bulk_s2g(void* dst, uint32_t src, uint32_t bytes) {
  asm volatile("cp.async.bulk.global.shared::cta.bulk_group [%0], [%1], %2;" ::"l"(dst), "r"(src), "r"(bytes) : "memory");
}
__device__ __forceinline__ void bulk_commit_wait() {
  asm volatile("cp.async.bulk.commit_group;" ::: "memory");
  asm volatile("cp.async.bulk.wait_group 0;" ::: "memory");
}
__device__ __forceinline__ void mbx_put(uint32_t* p, uint32_t v) { asm volatile("st.relaxed.gpu.global.b32 [%0], %1;" ::"l"(p), "r"(max(~v, 1u)) : "memory"); }
__device__ __forceinline__ uint32_t mbx_ld(const uint32_t* p) { uint32_t v; asm volatile("ld.relaxed.gpu.global.b32 %0, [%1];" : "=r"(v) : "l"(p) : "memory"); return v; }
__device__ __forceinline__ uint4 mbx_ld4(const uint32_t* p) {
  uint4 v; asm volatile("ld.relaxed.gpu.global.v4.b32 {%0, %1, %2, %3}, [%4];" : "=r"(v.x), "=r"(v.y), "=r"(v.z), "=r"(v.w) : "l"(p) : "memory"); return v;
}
__device__ __forceinline__ void stat_put(uint2* p, float m, float q) {
  asm volatile("st.relaxed.gpu.global.v2.b32 [%0], {%1, %2};" ::"l"(p), "r"(__float_as_uint(m)), "r"(__float_as_uint(q) & 0x7FFFFFFFu) : "memory");
}
__device__ __forceinline__ void stat_get(const uint2* p, float n0, float n1, float inv, float (&rs)[2], float (&mr)[2]) {
  uint4 v[2];
  int it = 0;
  do {
    v[0] = mbx_ld4((const uint32_t*)p); v[1] = mbx_ld4((const uint32_t*)(p + 64));
    if (++it > SPIN_LIMIT) __trap();
  } while (__any_sync(0xffffffffu, (int)(v[0].y | v[0].w | v[1].y | v[1].w) < 0));
#pragma unroll
  for (int h = 0; h < 2; h++) {
    const float ma = __uint_as_float(v[h].x), mb = __uint_as_float(v[h].z);
    float m = n0 * ma + n1 * mb;
    m += __shfl_xor_sync(0xffffffffu, m, 1); m += __shfl_xor_sync(0xffffffffu, m, 2);
    m *= inv;
    float q = __uint_as_float(v[h].y) + __uint_as_float(v[h].w) + n0 * (ma - m) * (ma - m) + n1 * (mb - m) * (mb - m);
    q += __shfl_xor_sync(0xffffffffu, q, 1); q += __shfl_xor_sync(0xffffffffu, q, 2);
    rs[h] = rsqrtf(q * inv + 1e-5f); mr[h] = -m * rs[h];
  }
}
__device__ __forceinline__ float silu_bf(bf16 c) { float v = __bfloat162float(c); return __bfloat162float(__float2bfloat16(v / (1.f + __expf(-v)))); }
__device__ __forceinline__ void ln_frags(uint32_t (&F)[16], const uint32_t (&ad)[4], uint32_t cs, const uint32_t (&ln)[4]) {
#pragma unroll
  for (int kk = 0; kk < 4; kk++) ldsm4(F + 4 * kk, ad[kk]);
#pragma unroll
  for (int kk = 0; kk < 4; kk++) {
    uint4 m = lds128(cs + kk * 64);
    F[4 * kk] = fma_bf16x2(fma_bf16x2(F[4 * kk], ln[0], ln[1]), m.x, m.z);
    F[4 * kk + 1] = fma_bf16x2(fma_bf16x2(F[4 * kk + 1], ln[2], ln[3]), m.x, m.z);
    F[4 * kk + 2] = fma_bf16x2(fma_bf16x2(F[4 * kk + 2], ln[0], ln[1]), m.y, m.w);
    F[4 * kk + 3] = fma_bf16x2(fma_bf16x2(F[4 * kk + 3], ln[2], ln[3]), m.y, m.w);
  }
#pragma unroll
  for (int i = 0; i < 16; i++) asm volatile("" : "+r"(F[i])::"memory");
}
template <int H, int X, int N> __device__ __forceinline__ void xred(float (&v)[N], int lane) {
  const bool up = lane & X;
#pragma unroll
  for (int i = 0; i < H; i++) {
    float keep = up ? v[i + H] : v[i], send = up ? v[i] : v[i + H];
    v[i] = keep + __shfl_xor_sync(0xffffffffu, send, X);
  }
}

__device__ __forceinline__ void wg_ss64(float (&d)[32], uint64_t da, uint64_t db, int scale_d) {
  asm volatile("{.reg .pred p; setp.ne.b32 p, %34, 0;\n wgmma.mma_async.sync.aligned.m64n64k16.f32.bf16.bf16 {"
      "%0, %1, %2, %3, %4, %5, %6, %7, %8, %9, %10, %11, %12, %13, %14, %15, %16, %17, %18, %19, %20, %21, %22, %23, %24, %25, %26, %27, %28, %29, %30, %31"
      "}, %32, %33, p, 1, 1, 0, 0;}\n"
    : "+f"(d[0]), "+f"(d[1]), "+f"(d[2]), "+f"(d[3]), "+f"(d[4]), "+f"(d[5]), "+f"(d[6]), "+f"(d[7]), "+f"(d[8]), "+f"(d[9]), "+f"(d[10]), "+f"(d[11]),
      "+f"(d[12]), "+f"(d[13]), "+f"(d[14]), "+f"(d[15]), "+f"(d[16]), "+f"(d[17]), "+f"(d[18]), "+f"(d[19]), "+f"(d[20]), "+f"(d[21]), "+f"(d[22]),
      "+f"(d[23]), "+f"(d[24]), "+f"(d[25]), "+f"(d[26]), "+f"(d[27]), "+f"(d[28]), "+f"(d[29]), "+f"(d[30]), "+f"(d[31])
    : "l"(da), "l"(db), "r"(scale_d));
}

__device__ __forceinline__ void wg_rs24_t(float (&d)[12], uint32_t a0, uint32_t a1, uint32_t a2, uint32_t a3, uint64_t db, int scale_d) {
  asm volatile("{.reg .pred p; setp.ne.b32 p, %17, 0;\n wgmma.mma_async.sync.aligned.m64n24k16.f32.bf16.bf16 {"
      "%0, %1, %2, %3, %4, %5, %6, %7, %8, %9, %10, %11"
      "}, {%12, %13, %14, %15}, %16, p, 1, 1, 1;}\n"
    : "+f"(d[0]), "+f"(d[1]), "+f"(d[2]), "+f"(d[3]), "+f"(d[4]), "+f"(d[5]), "+f"(d[6]), "+f"(d[7]), "+f"(d[8]), "+f"(d[9]), "+f"(d[10]), "+f"(d[11])
    : "r"(a0), "r"(a1), "r"(a2), "r"(a3), "l"(db), "r"(scale_d));
}

__device__ __forceinline__ void wg_rs128_t(float (&d)[64], uint32_t a0, uint32_t a1, uint32_t a2, uint32_t a3, uint64_t db, int scale_d) {
  asm volatile("{.reg .pred p; setp.ne.b32 p, %69, 0;\n wgmma.mma_async.sync.aligned.m64n128k16.f32.bf16.bf16 {"
      "%0, %1, %2, %3, %4, %5, %6, %7, %8, %9, %10, %11, %12, %13, %14, %15, %16, %17, %18, %19, %20, %21, %22, %23, %24, %25, %26, %27, %28, %29, %30, %31, "
      "%32, %33, %34, %35, %36, %37, %38, %39, %40, %41, %42, %43, %44, %45, %46, %47, %48, %49, %50, %51, %52, %53, %54, %55, %56, %57, %58, %59, %60, %61, "
      "%62, %63"
      "}, {%64, %65, %66, %67}, %68, p, 1, 1, 1;}\n"
    : "+f"(d[0]), "+f"(d[1]), "+f"(d[2]), "+f"(d[3]), "+f"(d[4]), "+f"(d[5]), "+f"(d[6]), "+f"(d[7]), "+f"(d[8]), "+f"(d[9]), "+f"(d[10]), "+f"(d[11]),
      "+f"(d[12]), "+f"(d[13]), "+f"(d[14]), "+f"(d[15]), "+f"(d[16]), "+f"(d[17]), "+f"(d[18]), "+f"(d[19]), "+f"(d[20]), "+f"(d[21]), "+f"(d[22]),
      "+f"(d[23]), "+f"(d[24]), "+f"(d[25]), "+f"(d[26]), "+f"(d[27]), "+f"(d[28]), "+f"(d[29]), "+f"(d[30]), "+f"(d[31]), "+f"(d[32]), "+f"(d[33]),
      "+f"(d[34]), "+f"(d[35]), "+f"(d[36]), "+f"(d[37]), "+f"(d[38]), "+f"(d[39]), "+f"(d[40]), "+f"(d[41]), "+f"(d[42]), "+f"(d[43]), "+f"(d[44]),
      "+f"(d[45]), "+f"(d[46]), "+f"(d[47]), "+f"(d[48]), "+f"(d[49]), "+f"(d[50]), "+f"(d[51]), "+f"(d[52]), "+f"(d[53]), "+f"(d[54]), "+f"(d[55]),
      "+f"(d[56]), "+f"(d[57]), "+f"(d[58]), "+f"(d[59]), "+f"(d[60]), "+f"(d[61]), "+f"(d[62]), "+f"(d[63])
    : "r"(a0), "r"(a1), "r"(a2), "r"(a3), "l"(db), "r"(scale_d));
}

__device__ __forceinline__ void wg_rs64_t(float (&d)[32], uint32_t a0, uint32_t a1, uint32_t a2, uint32_t a3, uint64_t db, int scale_d) {
  asm volatile("{.reg .pred p; setp.ne.b32 p, %37, 0;\n wgmma.mma_async.sync.aligned.m64n64k16.f32.bf16.bf16 {"
      "%0, %1, %2, %3, %4, %5, %6, %7, %8, %9, %10, %11, %12, %13, %14, %15, %16, %17, %18, %19, %20, %21, %22, %23, %24, %25, %26, %27, %28, %29, %30, %31"
      "}, {%32, %33, %34, %35}, %36, p, 1, 1, 1;}\n"
    : "+f"(d[0]), "+f"(d[1]), "+f"(d[2]), "+f"(d[3]), "+f"(d[4]), "+f"(d[5]), "+f"(d[6]), "+f"(d[7]), "+f"(d[8]), "+f"(d[9]), "+f"(d[10]), "+f"(d[11]),
      "+f"(d[12]), "+f"(d[13]), "+f"(d[14]), "+f"(d[15]), "+f"(d[16]), "+f"(d[17]), "+f"(d[18]), "+f"(d[19]), "+f"(d[20]), "+f"(d[21]), "+f"(d[22]),
      "+f"(d[23]), "+f"(d[24]), "+f"(d[25]), "+f"(d[26]), "+f"(d[27]), "+f"(d[28]), "+f"(d[29]), "+f"(d[30]), "+f"(d[31])
    : "r"(a0), "r"(a1), "r"(a2), "r"(a3), "l"(db), "r"(scale_d));
}

__device__ __forceinline__ void wg_ss64_t(float (&d)[32], uint64_t da, uint64_t db, int scale_d) {
  asm volatile("{.reg .pred p; setp.ne.b32 p, %34, 0;\n wgmma.mma_async.sync.aligned.m64n64k16.f32.bf16.bf16 {"
      "%0, %1, %2, %3, %4, %5, %6, %7, %8, %9, %10, %11, %12, %13, %14, %15, %16, %17, %18, %19, %20, %21, %22, %23, %24, %25, %26, %27, %28, %29, %30, %31"
      "}, %32, %33, p, 1, 1, 0, 1;}\n"
    : "+f"(d[0]), "+f"(d[1]), "+f"(d[2]), "+f"(d[3]), "+f"(d[4]), "+f"(d[5]), "+f"(d[6]), "+f"(d[7]), "+f"(d[8]), "+f"(d[9]), "+f"(d[10]), "+f"(d[11]),
      "+f"(d[12]), "+f"(d[13]), "+f"(d[14]), "+f"(d[15]), "+f"(d[16]), "+f"(d[17]), "+f"(d[18]), "+f"(d[19]), "+f"(d[20]), "+f"(d[21]), "+f"(d[22]),
      "+f"(d[23]), "+f"(d[24]), "+f"(d[25]), "+f"(d[26]), "+f"(d[27]), "+f"(d[28]), "+f"(d[29]), "+f"(d[30]), "+f"(d[31])
    : "l"(da), "l"(db), "r"(scale_d));
}

__device__ __forceinline__ void wg_ss88_t(float (&d)[44], uint64_t da, uint64_t db, int scale_d) {
  asm volatile("{.reg .pred p; setp.ne.b32 p, %46, 0;\n wgmma.mma_async.sync.aligned.m64n88k16.f32.bf16.bf16 {"
      "%0, %1, %2, %3, %4, %5, %6, %7, %8, %9, %10, %11, %12, %13, %14, %15, %16, %17, %18, %19, %20, %21, %22, %23, %24, %25, %26, %27, %28, %29, %30, %31, "
      "%32, %33, %34, %35, %36, %37, %38, %39, %40, %41, %42, %43"
      "}, %44, %45, p, 1, 1, 0, 1;}\n"
    : "+f"(d[0]), "+f"(d[1]), "+f"(d[2]), "+f"(d[3]), "+f"(d[4]), "+f"(d[5]), "+f"(d[6]), "+f"(d[7]), "+f"(d[8]), "+f"(d[9]), "+f"(d[10]), "+f"(d[11]),
      "+f"(d[12]), "+f"(d[13]), "+f"(d[14]), "+f"(d[15]), "+f"(d[16]), "+f"(d[17]), "+f"(d[18]), "+f"(d[19]), "+f"(d[20]), "+f"(d[21]), "+f"(d[22]),
      "+f"(d[23]), "+f"(d[24]), "+f"(d[25]), "+f"(d[26]), "+f"(d[27]), "+f"(d[28]), "+f"(d[29]), "+f"(d[30]), "+f"(d[31]), "+f"(d[32]), "+f"(d[33]),
      "+f"(d[34]), "+f"(d[35]), "+f"(d[36]), "+f"(d[37]), "+f"(d[38]), "+f"(d[39]), "+f"(d[40]), "+f"(d[41]), "+f"(d[42]), "+f"(d[43])
    : "l"(da), "l"(db), "r"(scale_d));
}

#define QKV_SMEM (131072 + 4 * 24576 + 2048 + 512 + 128 + TSX)
__global__ void __launch_bounds__(288, 1) k_qkv(const bf16* __restrict__ x, const bf16* __restrict__ c, const bf16* __restrict__ wmod, const bf16* __restrict__ wqkv,
                                                const __grid_constant__ CUtensorMap tmX, const __grid_constant__ CUtensorMap tmW) {
  TS(1, 0);
  extern __shared__ __align__(1024) uint8_t smem_raw[];
  const uint32_t sA = smem_u32(smem_raw), sB = sA + 131072, sCS = sB + 98304, sRed = sCS + 2048;
  const uint32_t fullA = sRed + 512, fullB = fullA + 64, empty = fullB + 32;
  const int t = threadIdx.x, warp = __shfl_sync(0xffffffffu, t >> 5, 0), lane = t & 31;
  const int rb = blockIdx.x >> 3, ct = blockIdx.x & 7;
  pdl_launch();
  if (warp == 8) {
    auto loadA = [&](int kb) { mbar_expect(fullA + 8 * kb, 16384); tma_2d(sA + kb * 16384, &tmX, kb * 64, rb * 128, fullA + 8 * kb); };
    auto loadB = [&](int kb) {
      const int s = kb & 3;
      mbar_expect(fullB + 8 * s, 24576);
      for (int j = 0; j < 3; j++) tma_2d(sB + s * 24576 + j * 8192, &tmW, ct * 192 + j * 64, kb * 64, fullB + 8 * s);
    };
    if (lane == 0) {
      if (sA & 1023) __trap();
      for (int i = 0; i < 8; i++) mbar_init(fullA + 8 * i, 1);
      for (int i = 0; i < 4; i++) { mbar_init(fullB + 8 * i, 1); mbar_init(empty + 8 * i, 2); }
      fence_mbar_init();
      prefetch_l2(wqkv + blockIdx.x * 6144, 12288);
      for (int kb = 0; kb < 3; kb++) { loadA(kb); loadB(kb); }
    }
    __syncwarp();
    bar_sync(1, 288);
    if (lane == 0) {
      for (int kb = 3; kb < 8; kb++) {
        loadA(kb);
        if (kb < 4) loadB(kb);
      }
      for (int kb = 4; kb < 8; kb++) { mbar_wait(empty + 8 * (kb & 3), 0); loadB(kb); }
    }
    return;
  }
  if (t == 0 && blockIdx.x == 0) g_cnt[0] = 0;
  const int col0 = (blockIdx.x & 63) * 16, k0 = (blockIdx.x >> 6) * 256 + (t >> 1);
  const bf16 c0 = c[k0], c1 = c[k0 + 128];
  uint4 w[2], xv[2][2];
#pragma unroll
  for (int p = 0; p < 2; p++) w[p] = ldg128(wmod + (size_t)(k0 + p * 128) * 3072 + col0 + (t & 1) * 8);
  const int srow = rb * 128 + ct * 16 + warp * 2;
#pragma unroll
  for (int r = 0; r < 2; r++) { xv[r][0] = ldg128(x + (size_t)(srow + r) * DM + lane * 8); xv[r][1] = ldg128(x + (size_t)(srow + r) * DM + 256 + lane * 8); }
  {
    const float s0 = silu_bf(c0), s1 = silu_bf(c1);
    const uint32_t *q0 = (const uint32_t*)&w[0], *q1 = (const uint32_t*)&w[1];
    float acc[8];
#pragma unroll
    for (int i = 0; i < 4; i++) { acc[2 * i] = fmaf(s0, bf_lo(q0[i]), s1 * bf_lo(q1[i])); acc[2 * i + 1] = fmaf(s0, bf_hi(q0[i]), s1 * bf_hi(q1[i])); }
    xred<4, 8>(acc, lane);
    xred<2, 4>(acc, lane); xred<1, 2>(acc, lane);
    acc[0] += __shfl_xor_sync(0xffffffffu, acc[0], 16);
    if (lane < 16) sts32(sRed + warp * 64 + ((lane & 1) * 8 + (lane >> 1)) * 4, __float_as_uint(acc[0]));
    if (warp) bar_arrive(2, 256);
    else {
      bar_sync(2, 256);
      float v = 0.f;
#pragma unroll
      for (int i = 0; i < 4; i++) v += __uint_as_float(lds32(sRed + (lane >> 4) * 256 + i * 64 + (lane & 15) * 4));
      v += __shfl_xor_sync(0xffffffffu, v, 16);
#pragma unroll
      for (int i = 0; i < 4; i++) mbx_put(g_mbx + (i * 2 + (lane >> 4)) * 2048 + blockIdx.x * 16 + (lane & 15), __float_as_uint(v));
    }
  }
  {
    float sm[2], sq[2];
#pragma unroll
    for (int r = 0; r < 2; r++) {
      const uint32_t* u = (const uint32_t*)&xv[r][0];
      sm[r] = 0.f;
#pragma unroll
      for (int i = 0; i < 8; i++) sm[r] += bf_lo(u[i]) + bf_hi(u[i]);
    }
#pragma unroll
    for (int o = 16; o; o >>= 1) { sm[0] += __shfl_xor_sync(0xffffffffu, sm[0], o); sm[1] += __shfl_xor_sync(0xffffffffu, sm[1], o); }
#pragma unroll
    for (int r = 0; r < 2; r++) {
      const uint32_t* u = (const uint32_t*)&xv[r][0];
      sm[r] *= (1.f / DM); sq[r] = 0.f;
#pragma unroll
      for (int i = 0; i < 8; i++) { float a = bf_lo(u[i]) - sm[r], b = bf_hi(u[i]) - sm[r]; sq[r] = fmaf(a, a, sq[r]); sq[r] = fmaf(b, b, sq[r]); }
    }
#pragma unroll
    for (int o = 16; o; o >>= 1) { sq[0] += __shfl_xor_sync(0xffffffffu, sq[0], o); sq[1] += __shfl_xor_sync(0xffffffffu, sq[1], o); }
    if (lane < 8) {
      float rs = rsqrtf((lane & 1 ? sq[1] : sq[0]) * (1.f / DM) + 1e-5f);
      mbx_put(g_mbx + 8 * SEQ + srow * 4 + lane, pack_bf16(rs, -(lane & 1 ? sm[1] : sm[0]) * rs));
    }
  }
  TS(1, 1);
  const int q4 = lane & 3, r8 = lane >> 2;
  const int row = rb * 128 + warp * 16 + r8;
  uint32_t ln[4];
  {
    uint4 a, b;
    uint32_t d, e;
    const uint32_t *mp = g_mbx + ct * 2048 + t * 4, *rp = g_mbx + 8 * SEQ + (row >> 1) * 8 + (row & 1);
    int it = 0;
    do {
      a = mbx_ld4(mp); b = mbx_ld4(mp + 1024); d = mbx_ld(rp); e = mbx_ld(rp + 32);
      if (++it > SPIN_LIMIT) __trap();
    } while (__any_sync(0xffffffffu, !min(min(min(min(a.x, a.y), min(a.z, a.w)), min(min(b.x, b.y), min(b.z, b.w))), min(d, e))));
    const uint32_t o = sCS + ((t & 127) >> 2) * 64 + (t & 1) * 32 + (t & 2) * 2 + (t < 128 ? 8 : 0), one = t < 128 ? 0u : 0x3F803F80u;
    sts32(o, fma_bf16x2(pack_bf16(__uint_as_float(~a.x) + __uint_as_float(~b.x), __uint_as_float(~a.y) + __uint_as_float(~b.y)), 0x3F803F80u, one));
    sts32(o + 16, fma_bf16x2(pack_bf16(__uint_as_float(~a.z) + __uint_as_float(~b.z), __uint_as_float(~a.w) + __uint_as_float(~b.w)), 0x3F803F80u, one));
    ln[0] = __byte_perm(~d, 0, 0x1010); ln[1] = __byte_perm(~d, 0, 0x3232);
    ln[2] = __byte_perm(~e, 0, 0x1010); ln[3] = __byte_perm(~e, 0, 0x3232);
  }
  bar_sync(1, 288);
  TS(1, 3);
  float acc[96];
#pragma unroll
  for (int i = 0; i < 96; i++) acc[i] = 0.f;
  reg_fence(acc);
  uint32_t F0[16], F1[16], ad[4];
#pragma unroll
  for (int kk = 0; kk < 4; kk++) ad[kk] = sA + (warp * 16 + (lane & 15)) * 128 + (((kk * 2 + (lane >> 4)) ^ (lane & 7)) << 4);
  uint32_t cs = sCS + q4 * 16;
  const uint64_t dB = mk_desc(sB, 8192, 1024, 1);
  const long long tc0 = clock64();
  auto step = [&](uint32_t (&F)[16], int kb) {
    wg_wait<1>();
    if (kb >= 2 && kb < 6 && (t & 127) == 0) mbar_arrive(empty + 8 * (kb - 2));
    ln_frags(F, ad, cs, ln);
#pragma unroll
    for (int kk = 0; kk < 4; kk++) ad[kk] += 16384;
    cs += 256;
    mbar_wait2(fullB + 8 * (kb & 3), kb >> 2, fullA + 8 * min(kb + 1, 7));
    bar_sync(3 + (warp >> 2), 256);
    wg_fence();
#pragma unroll
    for (int kk = 0; kk < 4; kk++) {
      wg_rs128_t(*(float(*)[64])acc, F[4 * kk], F[4 * kk + 1], F[4 * kk + 2], F[4 * kk + 3], dB + (kb & 3) * 1536 + kk * 128, 1);
      wg_rs64_t(*(float(*)[32])(acc + 64), F[4 * kk], F[4 * kk + 1], F[4 * kk + 2], F[4 * kk + 3], dB + (kb & 3) * 1536 + 1024 + kk * 128, 1);
    }
    wg_commit();
    if (kb < 7 || warp < 4) bar_arrive(4 - (warp >> 2), 256);
  };
  if (warp >= 4) bar_arrive(3, 256);
  mbar_wait(fullA, 0);
#pragma unroll 1
  for (int kb = 0; kb < 8; kb += 2) { step(F0, kb); step(F1, kb + 1); }
  wg_wait<0>();
  reg_fence(acc);
  TS(1, 4);
  uint32_t* qp = (uint32_t*)(g_qkv + ((size_t)ct * 24 * SEQ + rb * 128 + warp * 16) * 8) + lane;
  float nr[24];
#pragma unroll
  for (int hs = 0; hs < 12; hs++) {
    const float sc = ct * 12 + hs < 32 ? 0.25f * 1.4426950408889634f : 1.f;
    float v[8];
#pragma unroll
    for (int i = 0; i < 8; i++) v[i] = acc[hs * 8 + i] * sc;
#pragma unroll
    for (int i = 0; i < 4; i++) qp[(hs * 2 + (i >> 1)) * SEQ * 4 + (i & 1) * 32] = pack_bf16(v[2 * i], v[2 * i + 1]);
    nr[hs * 2] = fmaf(v[0], v[0], fmaf(v[1], v[1], fmaf(v[4], v[4], v[5] * v[5])));
    nr[hs * 2 + 1] = fmaf(v[2], v[2], fmaf(v[3], v[3], fmaf(v[6], v[6], v[7] * v[7])));
  }
  xred<12, 2>(nr, lane); xred<6, 1>(nr, lane);
  uint32_t m[3];
#pragma unroll
  for (int i = 0; i < 3; i++) m[i] = max(__float_as_uint(nr[2 * i]) & 0x7FFFFFFFu, __float_as_uint(nr[2 * i + 1]) & 0x7FFFFFFFu);
#pragma unroll
  for (int o = 4; o < 32; o <<= 1)
#pragma unroll
    for (int i = 0; i < 3; i++) m[i] = max(m[i], __shfl_xor_sync(0xffffffffu, m[i], o));
  if (r8 < 3) g_nrm[(ct * 12 + q4 * 3 + r8) * 128 + rb * 8 + warp] = __uint_as_float(r8 == 0 ? m[0] : r8 == 1 ? m[1] : m[2]);
  TS(1, 5);
}

__device__ __forceinline__ uint32_t exp2_pair_sw(float x0, float x1, uint32_t cm, uint32_t co) {
  float y0 = x0 + (65536.f + 127.f - 205.f / 128.f);
  float y1 = x1 + (65536.f + 496.f - 205.f / 128.f);
  uint32_t w = __float_as_uint(y1) * 65536u + __float_as_uint(y0);
  uint32_t m;
  asm("lop3.b32 %0, %1, %2, %3, 0xEA;" : "=r"(m) : "r"(w), "r"(cm), "r"(co));
  uint32_t p = fma_bf16x2(m, m, 0x40034003u);
  return w - m + p;
}
__device__ __forceinline__ uint32_t exp2_pair_hw(float x0, float x1) { return pack_bf16(ex2f(x0), ex2f(x1)); }
#define HW_MASK 0x2449u
#define ATT_SMEM (176 * 1040 + 1024 + TSX)
__device__ __forceinline__ uint64_t desc2(uint32_t lo, uint32_t hi) { uint64_t d; asm("mov.b64 %0, {%1, %2};" : "=l"(d) : "r"(lo), "r"(hi)); return d; }

template <int N> __device__ __forceinline__ void desc_add(uint64_t& d) {
  asm("{.reg .b32 lo, hi; mov.b64 {lo, hi}, %0; add.u32 lo, lo, %1; mov.b64 %0, {lo, hi};}" : "+l"(d) : "n"(N));
}
__device__ __forceinline__ void attn_store(float (&O)[12], bf16* op) {
  float r0 = 1.f / O[8], r1 = 1.f / O[10];
  *(uint32_t*)(op) = pack_bf16(O[0] * r0, O[1] * r0);
  *(uint32_t*)(op + 64) = pack_bf16(O[2] * r1, O[3] * r1);
  *(uint32_t*)(op + 512) = pack_bf16(O[4] * r0, O[5] * r0);
  *(uint32_t*)(op + 512 + 64) = pack_bf16(O[6] * r1, O[7] * r1);
}
struct AttOff { uint32_t k[2], v[8]; };
__device__ __forceinline__ void attn_fast(uint32_t sK, uint32_t sQ, uint32_t bar, bf16* op, bool first, const AttOff& off) {
  float S[32], O[12];
  uint32_t P0[16], P1[16];
#pragma unroll
  for (int i = 0; i < 12; i++) O[i] = 0.f;
#pragma unroll
  for (int i = 0; i < 32; i++) S[i] = 0.f;
  reg_fence(O); reg_fence(S);
  const uint32_t co = off.k[0] * (0x3F803F80u / 64);
  const uint64_t dQ = mk_desc(sQ, 8192, 128, 0);
  uint64_t dK[2], dV[8];
#pragma unroll
  for (int i = 0; i < 2; i++) dK[i] = mk_desc(sK, 32768, 128, 0) + off.k[i];
#pragma unroll
  for (int i = 0; i < 8; i++) dV[i] = mk_desc(sK + 65536, 128, 32768, 0) + off.v[i];
  wg_fence();
  wg_ss64(S, dQ, mk_desc(sK, 32768, 128, 0), 0);
  wg_commit();
  wg_commit();
  auto step = [&](uint32_t (&P)[16], int h, bool last) {
    wg_wait<1>();
    reg_fence(S);
#pragma unroll
    for (int j = 0; j < 16; j++) P[j] = (((HW_MASK) >> j) & 1) ? exp2_pair_hw(S[2 * j], S[2 * j + 1]) : exp2_pair_sw(S[2 * j], S[2 * j + 1], 0x007F007Fu, co);
    wg_fence();
    if (!last) {
      wg_ss64(S, dQ, dK[h], 0);
      desc_add<128>(dK[h]);
      wg_commit();
    }
#pragma unroll
    for (int kk = 0; kk < 4; kk++) { wg_rs24_t(O, P[4 * kk], P[4 * kk + 1], P[4 * kk + 2], P[4 * kk + 3], dV[h * 4 + kk], 1); desc_add<128>(dV[h * 4 + kk]); }
    wg_commit();
  };
#pragma unroll 1
  for (int c = 0; c < 4; c++) {
    if (first) mbar_wait(bar + 8 * c, 0);
#pragma unroll 1
    for (int i = c == 3; i < 4; i++) {
      step(P0, 0, false);
      step(P1, 1, false);
    }
  }
  step(P0, 0, false);
  step(P1, 1, true);
  wg_wait<0>();
  reg_fence(O);
  attn_store(O, op);
}
__device__ __forceinline__ void attn_safe(uint32_t sK, uint32_t sQ, uint32_t bar, bf16* op) {
  float S[32], O[12];
  uint32_t P[16];
#pragma unroll
  for (int i = 0; i < 12; i++) O[i] = 0.f;
#pragma unroll
  for (int i = 0; i < 32; i++) S[i] = 0.f;
  float m0 = -INFINITY, m1 = -INFINITY;
  const uint64_t dQ = mk_desc(sQ, 8192, 128, 0), dK = mk_desc(sK, 32768, 128, 0), dV = mk_desc(sK + 65536, 128, 32768, 0);
#pragma unroll 1
  for (int i = 0; i < 32; i++) {
    mbar_wait(bar + 8 * (i >> 3), 0);
    reg_fence(S);
    wg_fence();
    wg_ss64(S, dQ, dK + i * 64, 0);
    wg_commit();
    wg_wait<0>();
    reg_fence(S);
    float a = m0, b = m1;
#pragma unroll
    for (int j = 0; j < 8; j++) { a = fmaxf(a, fmaxf(S[4 * j], S[4 * j + 1])); b = fmaxf(b, fmaxf(S[4 * j + 2], S[4 * j + 3])); }
    a = fmaxf(a, __shfl_xor_sync(0xffffffffu, a, 1)); b = fmaxf(b, __shfl_xor_sync(0xffffffffu, b, 1));
    a = fmaxf(a, __shfl_xor_sync(0xffffffffu, a, 2)); b = fmaxf(b, __shfl_xor_sync(0xffffffffu, b, 2));
    float f0 = m0 == a ? 1.f : ex2f(m0 - a), f1 = m1 == b ? 1.f : ex2f(m1 - b);
    m0 = a; m1 = b;
#pragma unroll
    for (int j = 0; j < 3; j++) { O[4 * j] *= f0; O[4 * j + 1] *= f0; O[4 * j + 2] *= f1; O[4 * j + 3] *= f1; }
#pragma unroll
    for (int j = 0; j < 8; j++) { P[2 * j] = exp2_pair_hw(S[4 * j] - a, S[4 * j + 1] - a); P[2 * j + 1] = exp2_pair_hw(S[4 * j + 2] - b, S[4 * j + 3] - b); }
    reg_fence(O);
    wg_fence();
#pragma unroll
    for (int kk = 0; kk < 4; kk++) wg_rs24_t(O, P[4 * kk], P[4 * kk + 1], P[4 * kk + 2], P[4 * kk + 3], dV + i * 64 + kk * 16, 1);
    wg_commit();
    wg_wait<0>();
    reg_fence(O);
  }
  attn_store(O, op);
}

__device__ __forceinline__ void side_job(uint32_t sm, uint32_t sMod, const bf16* __restrict__ c, const bf16* __restrict__ wmod, const bf16* __restrict__ w_in) {
  const int t = threadIdx.x, j = blockIdx.x;
  sts32(sm + t * 4, __float_as_uint(silu_bf(c[t])));
  __syncthreads();
  float acc[8];
#pragma unroll
  for (int i = 0; i < 8; i++) acc[i] = 0.f;
  const int grp = (t & 63) >> 4, col = 1024 + grp * 512 + j * 128 + (t & 15) * 8;
  const bf16* wp = wmod + (size_t)(t >> 6) * 64 * 3072 + col;
#pragma unroll 16
  for (int k = 0; k < 64; k++) {
    const uint4 w = ldg128(wp + k * 3072);
    const float s = __uint_as_float(lds32(sm + ((t >> 6) * 64 + k) * 4));
    const uint32_t* q = (const uint32_t*)&w;
#pragma unroll
    for (int i = 0; i < 4; i++) { acc[2 * i] = fmaf(s, bf_lo(q[i]), acc[2 * i]); acc[2 * i + 1] = fmaf(s, bf_hi(q[i]), acc[2 * i + 1]); }
  }
#pragma unroll
  for (int i = 0; i < 8; i++) sts32(sm + 2048 + (t >> 6) * 2048 + (i * 64 + (t & 63)) * 4, __float_as_uint(acc[i]));
  __syncthreads();
  float v = 0.f;
#pragma unroll
  for (int i = 0; i < 8; i++) v += __uint_as_float(lds32(sm + 2048 + i * 2048 + t * 4));
  v = __bfloat162float(__float2bfloat16(v));
  const bf16 vb = __float2bfloat16(grp == 2 ? v + 1.f : v);
  g_mod[col + (t >> 6)] = vb;
  if (grp == 1 || grp == 2) sts32(sMod + ((t & 15) * 8 + (t >> 6)) * 8 + (grp & 1) * 4, __float_as_uint(__bfloat162float(vb)));
  const int kh = t >= 176, ch = t - kh * 176;
  float v1[8], v2[8];
#pragma unroll
  for (int i = 0; i < 8; i++) v1[i] = v2[i] = 0.f;
  for (int kb = 0; kb < 2; kb++) {
    __syncthreads();
    if (t < 352) {
#pragma unroll 16
      for (int k = kh * 32; k < kh * 32 + 32; k++) {
        uint4 w = ch < 172 ? ldg128(w_in + (size_t)(j * 128 + kb * 64 + k) * (2 * FH) + ch * 8) : make_uint4(0, 0, 0, 0);
        const float cc = __uint_as_float(lds32(sMod + (kb * 64 + k) * 8)), sb = __uint_as_float(lds32(sMod + (kb * 64 + k) * 8 + 4));
        uint32_t* q = (uint32_t*)&w;
#pragma unroll
        for (int i = 0; i < 4; i++) {
          v2[2 * i] = fmaf(sb, bf_lo(q[i]), v2[2 * i]); v2[2 * i + 1] = fmaf(sb, bf_hi(q[i]), v2[2 * i + 1]);
          q[i] = pack_bf16(cc * bf_lo(q[i]), cc * bf_hi(q[i]));
          v1[2 * i] += bf_lo(q[i]); v1[2 * i + 1] += bf_hi(q[i]);
        }
        sts128(sm + ch * 1040 + k * 16, w);
      }
    }
    fence_async_smem();
    __syncthreads();
    if (t < 176) {
      const int h = t >= 88, f = t - h * 88, ct = f / 11;
      bulk_s2g(g_win + (((ct * 2 + h) * 8 + 2 * j + kb) * 11 + f - ct * 11) * 512, sm + (f < 86 ? f + (h ? 0 : 86) : 172) * 1040, 1024);
      bulk_commit_wait();
    }
  }
  __syncthreads();
  if (kh && t < 352)
#pragma unroll
    for (int i = 0; i < 8; i++) { sts32(sm + (i * 352 + ch) * 4, __float_as_uint(v1[i])); sts32(sm + (i * 352 + t) * 4, __float_as_uint(v2[i])); }
  __syncthreads();
  if (t < 176) {
    float2* d = (float2*)g_v + j * 1408 + (t < 86 ? t : t < 172 ? t + 2 : t < 174 ? t - 86 : t) * 8;
#pragma unroll
    for (int i = 0; i < 8; i++) d[i] = make_float2(v1[i] + __uint_as_float(lds32(sm + (i * 352 + t) * 4)), v2[i] + __uint_as_float(lds32(sm + (i * 352 + 176 + t) * 4)));
  }
}

__global__ void __launch_bounds__(512, 1) k_attn(const bf16* __restrict__ c, const bf16* __restrict__ wmod, const bf16* __restrict__ w_in, const bf16* __restrict__ w_sp, const bf16* __restrict__ w_out, const bf16* __restrict__ wo, const __grid_constant__ AttOff off) {
  TS(2, 0);
  extern __shared__ uint8_t smem_raw[];
  __shared__ __align__(8) uint64_t bars[4];
  __shared__ __align__(16) uint32_t s_nrm[288];
  const uint32_t sK = (smem_u32(smem_raw) + 1023) & ~1023u, sQ = sK + 65536 + 98304;
  const uint32_t bar = smem_u32(bars);
  const int t = threadIdx.x, warp = __shfl_sync(0xffffffffu, t >> 5, 0), lane = t & 31;
  if (blockIdx.x < 4) { pdl_launch(); side_job(sK, smem_u32(s_nrm), c, wmod, w_in); TS(2, 5); return; }
  const int bid = blockIdx.x - 4, head = bid >> 2, quarter = bid & 3;
  if (t == 0) {
    for (int i = 0; i < 4; i++) mbar_init(bar + 8 * i, 1);
    fence_mbar_init();
    for (int i = 0; i < 4; i++) mbar_expect(bar + 8 * i, i == 0 ? 49152 + 1152 + 2048 : i == 3 ? 32768 - 2048 : 32768);
  }
#pragma unroll
  for (int i = 0; i < 4; i++) sts128(sK + 131072 + i * 8192 + t * 16, make_uint4(0x3F803F80u, 0x3F803F80u, 0x3F803F80u, 0x3F803F80u));
  if (t < 128) *(uint4*)(g_st + bid * 256 + t * 2) = make_uint4(~0u, ~0u, ~0u, ~0u);
  else if (t < 134) g_flag[bid * 6 + t - 128] = 0;
  fence_async_smem();
  __syncthreads();
  TS(2, 1);
  pdl_wait();
  pdl_launch();
  TS(2, 2);
  auto kv = [&](int c, int pl) {
    const int o = c * 8192 + (pl < 2 && c ? 1024 : 0), e = c * 8192 + 8192 + (pl < 2 && c < 3 ? 1024 : 0);
    bulk_g2s(sK + pl * 32768 + o, g_qkv + ((32 + (pl >> 1) * 32 + head) * 2 + (pl & 1)) * (SEQ * 8) + o / 2, e - o, bar + 8 * c);
  };
  if (lane == 0) {
    if (warp < 4) kv(0, warp);
    else if (warp < 6) bulk_g2s(sQ + (warp & 1) * 8192, g_qkv + (head * 2 + (warp & 1)) * (SEQ * 8) + quarter * 4096, 8192, bar);
    else if (warp < 8) bulk_g2s(smem_u32(s_nrm) + (warp & 1) * 512, g_nrm + (32 + (warp & 1) * 32 + head) * 128, 512, bar);
    else if (warp == 8) bulk_g2s(smem_u32(s_nrm) + 1024, g_nrm + head * 128 + quarter * 32, 128, bar);
  }
  __syncwarp();
  mbar_wait(bar, 0);
  if (lane == 0 && warp < 12) kv(1 + (warp >> 2), warp & 3);
  __syncwarp();
  if (t == 128) {
    int l = bid;
    if (l < 32) prefetch_l2(wo + l * 8192, 16384);
    else if (l < 75) prefetch_l2(w_out + (l - 32) * 8192, 16384);
    for (int i = 0; i < 4; i++) prefetch_l2(w_sp + (size_t)(l * 4 + i) * 8192, 16384);
  }
  if (t >= 256 && t < 304) *(uint4*)(g_mbx + bid * 192 + (t - 256) * 4) = make_uint4(0, 0, 0, 0);
  const uint4 nk = *(const uint4*)(s_nrm + lane * 4), nv = *(const uint4*)(s_nrm + 128 + lane * 4);
  const float mk = __uint_as_float(__reduce_max_sync(0xffffffffu, max(max(nk.x, nk.y), max(nk.z, nk.w))));
  const float mv = __uint_as_float(__reduce_max_sync(0xffffffffu, max(max(nv.x, nv.y), max(nv.z, nv.w))));
  const float mq = __uint_as_float(__reduce_max_sync(0xffffffffu, s_nrm[256 + lane]));
  const bool fast = (mq * mk <= 3900.f) && (mv <= 1e24f);
  const int wg = __shfl_sync(0xffffffffu, warp >> 2, 0);
  TS(2, 3); TSC(2, 0);
#pragma unroll 1
  for (int mt = 0; mt < 2; mt++) {
    const int rb64 = quarter * 8 + wg * 2 + mt, r = (warp & 3) * 16 + (lane >> 2);
    bf16* op = g_o + (rb64 * 64 + head * 2) * 512 + r * 8 + (lane & 3) * 2;
    const uint32_t sq = sQ + (wg * 2 + mt) * 1024;
    if (fast) attn_fast(sK, sq, bar, op, mt == 0, off);
    else attn_safe(sK, sq, bar, op);
  }
  TS(2, 5); TSC(2, 1);
}

#define POST_SMEM (131072 + 90112 + 1408 + 512 + TSX)
template <int N> __device__ __forceinline__ void put_tile(bf16* d, const uint32_t (&p)[N]) {
#pragma unroll
  for (int j = 0; j < N / 2; j++) { *(uint32_t*)(d + j * 512) = p[2 * j]; *(uint32_t*)(d + j * 512 + 64) = p[2 * j + 1]; }
}
template <int N> __device__ __forceinline__ void widen(float (&f)[2 * N], const uint32_t (&p)[N]) {
#pragma unroll
  for (int j = 0; j < N; j++) { f[2 * j] = bf_lo(p[j]); f[2 * j + 1] = bf_hi(p[j]); }
  reg_fence(f);
}
__device__ __forceinline__ void gate_add(uint32_t (&r)[16], const float (&x)[32], const float (&g)[16], const float (&a)[32]) {
#pragma unroll
  for (int j = 0; j < 16; j++) r[j] = pack_bf16(fmaf(g[j & ~1], a[2 * j], x[2 * j]), fmaf(g[j | 1], a[2 * j + 1], x[2 * j + 1]));
}
__device__ __forceinline__ void publish(uint32_t* flag) {
  asm volatile("red.release.gpu.global.add.u32 [%0], 1;" ::"l"(flag) : "memory");
}
__device__ __forceinline__ void flag_wait(const uint32_t* p, uint32_t n, uint32_t need, uint32_t& ready) {
  if ((ready & need) == need) return;
#pragma unroll 1
  for (int it = 0; it < SPIN_LIMIT; it++) {
    uint32_t v;
    asm volatile("ld.acquire.gpu.global.b32 %0, [%1];" : "=r"(v) : "l"(p) : "memory");
    ready = __ballot_sync(0xffffffffu, v == n);
    if ((ready & need) == need) { asm volatile("fence.proxy.async.global;" ::: "memory"); return; }
  }
  __trap();
}
__device__ __forceinline__ int sm_role() {
  uint32_t s; asm("mov.u32 %0, %%smid;" : "=r"(s));
  int g, l;
  if (s < 64) { g = (s >> 1) & 7; l = (s >> 4) * 2 + (s & 1); }
  else if (s < 120) { const int q = (s - 64) >> 1; g = 1 + q % 7; l = 8 + q / 7 * 2 + (s & 1); }
  else { g = 0; l = s - 112; }
  if ((g & 1) && g != 3 && g != 5) g = 8 - g;
  return s < 128 ? ((g >> 1) * 4 + (l >> 2)) * 8 + (g & 1) * 4 + (l & 3) : -1;
}
__global__ void __launch_bounds__(384, 1)
k_post(const bf16* __restrict__ x, const bf16* __restrict__ b_sp, const __grid_constant__ CUtensorMap tmWo, const __grid_constant__ CUtensorMap tmS,
       const __grid_constant__ CUtensorMap tmWout, const __grid_constant__ CUtensorMap tmOut) {
  TS(3, 0);
  extern __shared__ __align__(1024) uint8_t smem_raw[];
  const uint32_t sA = smem_u32(smem_raw), sB = sA + 131072, sV = sB + 90112;
  const uint32_t full = sV + 1408, empty = full + 64, fullB = empty + 64, emptyB = fullB + 64, fullU = emptyB + 64;
  const int t = threadIdx.x, warp = __shfl_sync(0xffffffffu, t >> 5, 0), lane = t & 31;
  int role = blockIdx.x;
  if (gridDim.x == 132) {
    role = sm_role();
    if (t == 0) asm volatile("red.relaxed.gpu.global.add.u32 [%0], 1;" ::"l"(g_cnt) : "memory");
    if (role < 0) {
      if (t == 0) for (int it = 0; mbx_ld(g_cnt) < 132u; it++) { if (it > SPIN_LIMIT) __trap(); __nanosleep(200); }
      return;
    }
  }
  const int rb = role >> 3, ct = role & 7;
  if (t == 256) {
    if (sA & 1023) __trap();
    for (int i = 0; i < 8; i++) { mbar_init(full + 8 * i, 1); mbar_init(empty + 8 * i, 2); mbar_init(fullB + 8 * i, 1); mbar_init(emptyB + 8 * i, 2); }
    for (int i = 0; i < 11; i++) mbar_init(fullU + 8 * i, 1);
    fence_mbar_init();
    for (int i = 0; i < 8; i++) mbar_expect(full + 8 * i, i & 3 ? 8192 : 8192 + 65536);
    for (int i = 0; i < 4; i++) tma_2d(sA + (i & 1) * 65536 + (i >> 1) * 32768, &tmWo, (ct & 3) * 128 + (i & 1) * 64, (i >> 1) * 256, full + (i >> 1) * 32);
    for (int i = 0; i < 11; i++) mbar_expect(fullU + 8 * i, 8192);
    prefetch_tmap(&tmS); prefetch_tmap(&tmWout); prefetch_tmap(&tmOut);
  }
  const int wg = warp >> 2, q4 = lane & 3;
  const int row = rb * 128 + warp * 16 + (lane >> 2);
  const int ho = rb * 2 + (ct >> 2), co = (ct & 3) * 2 + wg;
  const int rowo = ho * 64 + (warp & 3) * 16 + (lane >> 2), col0 = co * 64 + q4 * 2;
  uint32_t xr[16];
  if (warp < 8) {
#pragma unroll
    for (int j = 0; j < 8; j++) {
      xr[2 * j] = __ldg((const uint32_t*)(x + (size_t)rowo * DM + col0 + j * 8));
      xr[2 * j + 1] = __ldg((const uint32_t*)(x + (size_t)(rowo + 8) * DM + col0 + j * 8));
    }
  }
  __syncthreads();
  TS(3, 1);
  pdl_wait();
  TS(3, 2);
  if (warp >= 8) {
    const int p = warp - 8, hb = rb * 2 + (p & 1);
    auto loadA = [&](const bf16* src, int stride, int s) {
      bulk_g2s(sA + s * 16384, src, 8192, full + 8 * s); bulk_g2s(sA + s * 16384 + 8192, src + stride, 8192, full + 8 * s);
    };
    auto loadW = [&](int kb) {
      mbar_expect(fullB + 8 * (kb & 7), 11264);
      bulk_g2s(sB + (kb & 7) * 11264, g_win + (ct * 16 + kb) * 5632, 11264, fullB + 8 * (kb & 7));
    };
    if (lane == 0) {
      for (int kb = p; kb < 8; kb += 4) bulk_g2s(sB + (kb + 3) * 8192, g_o + ho * 32768 + kb * 4096, 8192, full + 8 * kb);
      const int q = p ^ 2;
      if (q >= 2) mbar_wait(empty + 8 * q - 8, 0);
      loadW(q);
      mbar_wait(empty + 8 * (q ? q + 4 : 3), 0);
      loadW(q + 4);
      mbar_wait(empty + 56, 0);
      mbar_expect(full + 8 * p, 16384); mbar_expect(full + 8 * p + 32, 16384);
    }
    __syncwarp();
    if (p >= 2) {
      bar_sync(p - 1, 160);
      if (lane == 0) { publish(g_flag + rb * 8 + (ct & 3) * 2 + (p & 1)); if (p == 2) TSA(24); }
      __syncwarp();
    }
    uint32_t ready = 0;
    for (int kb = p; kb < 8; kb += 4) {
      flag_wait(g_flag + rb * 8 + (lane & 7), 2, 1u << kb, ready);
      if (lane == 0) loadA(g_x1 + rb * 65536 + kb * 4096, 32768, kb);
      if (kb == 0) TSA(25);
      if (kb == 7) TSA(26);
    }
    const int rot = (rb >> 2) * 8;
    auto loadS = [&](int i) {
      const int s = i & 7;
      mbar_wait(empty + 8 * s, ((i >> 3) + 1) & 1);
      mbar_expect(full + 8 * s, 16384 + 11264);
      tma_2d(sA + s * 16384, &tmS, ((i + rot) & 31) * 64, rb * 128, full + 8 * s);
    };
    if (lane == 0) { mbar_wait(emptyB + 8 * p, 0); loadW(8 + p); mbar_wait(emptyB + 8 * p + 32, 0); loadW(12 + p); }
    if (lane == 0) loadS(p);
    __syncwarp();
    if (p >= 2) bar_sync(p - 1, 160);
    if (lane == 0) {
      if (p >= 2) publish(g_flag + 256 + ((ct >> 2) * 4 + (rb >> 2)) * 32);
      if (p == 2) TSA(27);
    }
    __syncwarp();
    ready = 0;
    const bf16* zp = g_z2 + ct * 32 * 5632;
    for (int i = p; i < 32; i += 4) {
      flag_wait(g_flag + 256 + ((ct >> 2) * 4 + (lane & 3)) * 32, 32, i < 8 ? 1u << (rb >> 2) : 15u, ready);
      if (lane == 0) {
        if (i >= 4) loadS(i);
        bulk_g2s(sB + (i & 7) * 11264, zp + ((i + rot) & 31) * 5632, 11264, full + 8 * (i & 7));
        if (i == 0) TSA(28);
        if (i == 7) TSA(29);
      }
    }
    auto loadF = [&](int j) {
      const int s = j & 7;
      mbar_wait(empty + 8 * s, j < 8);
      mbar_expect(full + 8 * s, 16384);
      for (int w = 0; w < 2; w++) tma_2d(sA + s * 16384 + w * 8192, &tmWout, (ct & 3) * 128 + w * 64, j * 64, full + 8 * s);
    };
    if (lane == 0) { loadF(p); loadF(p + 4); mbar_wait(empty + 56, 1); }
    __syncwarp();
    if (p >= 2) {
      bar_sync(p - 1, 160);
      if (lane == 0) {
        publish(g_flag + 512 + hb * 8 + ct);
        if (p == 2) TSA(30);
      }
      __syncwarp();
    }
    ready = 0;
    for (int j = p; j < 11; j += 4) {
      flag_wait(g_flag + 512 + ho * 8 + (lane & 7), 1, (1u << (j * 8 / 11)) | (1u << ((j * 8 + 7) / 11)), ready);
      if (lane == 0) {
        bulk_g2s(sB + j * 8192, g_u + ho * (88 * 512) + j * 4096, 8192, fullU + 8 * j);
        if (j >= 8) loadF(j);
        if (j == 0) TSA(31);
        if (j == 7) TSA(19);
      }
    }
  } else {
    const uint64_t dA0 = mk_desc(sA + wg * 8192, 1024, 128, 0), dAh = mk_desc(sB, 1024, 128, 0), dB64 = mk_desc(sA, 8192, 1024, 1), dB88 = mk_desc(sB, 128, 1024, 0);
    const bool rel = (t & 127) == 0;
    const int hb = rb * 2 + wg, tp = (warp & 3) * 128 + lane * 2;
    {
      uint32_t ga[8];
#pragma unroll
      for (int j = 0; j < 8; j++) ga[j] = *(const uint32_t*)(g_mod + 1024 + col0 + j * 8);
      float2 va, vb, vd, ve;
      if (t < 176) {
        const int h = t >= 88, c = t - h * 88;
        const float* p = g_v + (ct * 88 + c + (h ? 0 : 704)) * 2;
        va = *(const float2*)p; vb = *(const float2*)(p + 2816); vd = *(const float2*)(p + 5632); ve = *(const float2*)(p + 8448);
      }
      float acc[32];
#pragma unroll 1
      for (int kb = 0; kb < 8; kb++) {
        mbar_wait(full + 8 * kb, 0);
        if (kb == 0) TS(9, 6);
        if (kb == 7) TS(9, 7);
        wg_fence();
#pragma unroll
        for (int kk = 0; kk < 4; kk++) wg_ss64_t(acc, dAh + (kb + 3) * 512 + kk * 128, dB64 + wg * 4096 + kb * 512 + kk * 128, (kb | kk) != 0);
        wg_commit();
        if (kb) { wg_wait<1>(); if (rel) mbar_arrive(empty + 8 * kb - 8); }
      }
      float xf[32], gf[16];
      widen(xf, xr); widen(gf, ga);
      wg_wait<0>();
      reg_fence(acc);
      TS(3, 3);
      if (rel) mbar_arrive(empty + 56);
      gate_add(xr, xf, gf, acc);
      put_tile(g_x1 + (ho * 64 + co * 8) * 512 + tp, xr);
      bar_arrive(1 + wg, 160);
#pragma unroll
      for (int j = 0; j < 16; j++) asm volatile("" : "+r"(xr[j]));
      widen(acc, xr);
      float s0 = 0.f, s1 = 0.f;
#pragma unroll
      for (int j = 0; j < 8; j++) { s0 += acc[4 * j] + acc[4 * j + 1]; s1 += acc[4 * j + 2] + acc[4 * j + 3]; }
      s0 += __shfl_xor_sync(0xffffffffu, s0, 1); s1 += __shfl_xor_sync(0xffffffffu, s1, 1);
      s0 += __shfl_xor_sync(0xffffffffu, s0, 2); s1 += __shfl_xor_sync(0xffffffffu, s1, 2);
      s0 *= (1.f / 64); s1 *= (1.f / 64);
      float q0 = 0.f, q1 = 0.f;
#pragma unroll
      for (int j = 0; j < 8; j++) {
        float a = acc[4 * j] - s0, b = acc[4 * j + 1] - s0, c = acc[4 * j + 2] - s1, d = acc[4 * j + 3] - s1;
        q0 = fmaf(a, a, fmaf(b, b, q0)); q1 = fmaf(c, c, fmaf(d, d, q1));
      }
      q0 += __shfl_xor_sync(0xffffffffu, q0, 1); q1 += __shfl_xor_sync(0xffffffffu, q1, 1);
      q0 += __shfl_xor_sync(0xffffffffu, q0, 2); q1 += __shfl_xor_sync(0xffffffffu, q1, 2);
      if (q4 < 2) stat_put(g_st + (rowo + 8 * q4) * 8 + co, q4 ? s1 : s0, q4 ? q1 : q0);
      if (t < 176) {
        const uint32_t o = sV + (t >> 1) * 16 + (t & 1) * 4;
        sts32(o, __float_as_uint((va.x + vb.x) + (vd.x + ve.x))); sts32(o + 8, __float_as_uint((va.y + vb.y) + (vd.y + ve.y)));
      }
      bar_sync(3, 256);
    }
    TS(3, 4);
    float acc[44], ac1[44];
#pragma unroll 1
    for (int kb = 0; kb < 8; kb++) {
      mbar_wait2(full + 8 * kb, 1, fullB + 8 * kb);
      if (kb == 0) TS(8, 0);
      wg_fence();
#pragma unroll
      for (int kk = 0; kk < 4; kk++) wg_ss88_t(acc, dA0 + kb * 1024 + kk * 128, dB88 + kb * 704 + kk * 16, (kb | kk) != 0);
      wg_commit();
      if (kb == 6) { wg_wait<1>(); if ((t & 127) < 6) mbar_arrive(emptyB + 8 * lane); }
    }
    float rs[2], mr[2];
    stat_get(g_st + row * 8 + q4 * 2, 64.f, 64.f, 1.f / DM, rs, mr);
    auto pass2 = [&](int k0) {
#pragma unroll 1
      for (int kb = k0; kb < k0 + 4; kb++) {
        mbar_wait(fullB + 8 * kb, 1);
        wg_fence();
#pragma unroll
        for (int kk = 0; kk < 4; kk++) wg_ss88_t(ac1, dA0 + kb * 1024 + kk * 128, dB88 + kb * 704 + kk * 16, (kb | kk) != 0);
      }
      wg_commit();
    };
    wg_wait<0>();
    reg_fence(acc);
    if ((t & 127) < 2) mbar_arrive(emptyB + 48 + 8 * lane);
    TS(8, 1);
    const int nch = ct == 7 ? 9 : 11;
    auto act = [&](float (&a)[44], uint32_t v) {
#pragma unroll
      for (int j = 0; j < 11; j++) {
        const uint4 c = lds128(v + j * 64);
        a[4 * j] = gelu_tanh(fmaf(a[4 * j], rs[0], fmaf(mr[0], __uint_as_float(c.x), __uint_as_float(c.z))));
        a[4 * j + 1] = gelu_tanh(fmaf(a[4 * j + 1], rs[0], fmaf(mr[0], __uint_as_float(c.y), __uint_as_float(c.w))));
        a[4 * j + 2] = gelu_tanh(fmaf(a[4 * j + 2], rs[1], fmaf(mr[1], __uint_as_float(c.x), __uint_as_float(c.z))));
        a[4 * j + 3] = gelu_tanh(fmaf(a[4 * j + 3], rs[1], fmaf(mr[1], __uint_as_float(c.y), __uint_as_float(c.w))));
      }
    };
    act(acc, sV + q4 * 16);
    {
      float s0 = 0.f, s1 = 0.f;
#pragma unroll
      for (int j = 0; j < 11; j++) { s0 += acc[4 * j] + acc[4 * j + 1]; s1 += acc[4 * j + 2] + acc[4 * j + 3]; }
      s0 += __shfl_xor_sync(0xffffffffu, s0, 1); s1 += __shfl_xor_sync(0xffffffffu, s1, 1);
      s0 += __shfl_xor_sync(0xffffffffu, s0, 2); s1 += __shfl_xor_sync(0xffffffffu, s1, 2);
      const float ic = ct == 7 ? 1.f / 72 : 1.f / 88;
      s0 *= ic; s1 *= ic;
      float q0 = 0.f, q1 = 0.f;
#pragma unroll
      for (int j = 0; j < 11; j++) {
        if (j < nch) {
          float a = acc[4 * j] - s0, b = acc[4 * j + 1] - s0, c = acc[4 * j + 2] - s1, d = acc[4 * j + 3] - s1;
          q0 = fmaf(a, a, fmaf(b, b, q0)); q1 = fmaf(c, c, fmaf(d, d, q1));
        }
      }
      q0 += __shfl_xor_sync(0xffffffffu, q0, 1); q1 += __shfl_xor_sync(0xffffffffu, q1, 1);
      q0 += __shfl_xor_sync(0xffffffffu, q0, 2); q1 += __shfl_xor_sync(0xffffffffu, q1, 2);
      if (q4 < 2) stat_put(g_st + 8 * SEQ + (row + 8 * q4) * 8 + ct, q4 ? s1 : s0, q4 ? q1 : q0);
    }
    TS(8, 2);
    pass2(0);
    uint32_t pk[22];
    {
      float r2[2], m2[2];
      stat_get(g_st + 8 * SEQ + row * 8 + q4 * 2, 88.f, q4 == 3 ? 72.f : 88.f, 1.f / FH, r2, m2);
      wg_wait<0>();
      if ((t & 127) < 4) mbar_arrive(empty + lane * 8);
      TS(8, 3);
#pragma unroll
      for (int j = 0; j < 11; j++) {
        pk[2 * j] = j < nch ? pack_bf16(fmaf(acc[4 * j], r2[0], m2[0]), fmaf(acc[4 * j + 1], r2[0], m2[0])) : 0u;
        pk[2 * j + 1] = j < nch ? pack_bf16(fmaf(acc[4 * j + 2], r2[1], m2[1]), fmaf(acc[4 * j + 3], r2[1], m2[1])) : 0u;
      }
    }
    put_tile(g_z2 + (ct * 32 + hb) * 5632 + tp, pk);
    bar_arrive(1 + wg, 160);
    TS(8, 4);
    pass2(4);
    wg_wait<0>();
    reg_fence(ac1);
    if ((t & 127) < 4) mbar_arrive(empty + lane * 8 + 32);
    const float b0 = __bfloat162float(b_sp[row]), b1 = __bfloat162float(b_sp[row + 8]);
    act(ac1, sV + 704 + q4 * 16);
#pragma unroll
    for (int j = 0; j < 22; j++) { pk[j] = pack_bf16(ac1[2 * j], ac1[2 * j + 1]); acc[2 * j] = acc[2 * j + 1] = j & 1 ? b1 : b0; }
    widen(ac1, pk);
    reg_fence(acc);
    TS(8, 5);
    const uint64_t dAs = mk_desc(sA + wg * 8192, 16, 1024, 1);
#pragma unroll 1
    for (int i = 0; i < 32; i++) {
      const int s = i & 7;
      mbar_wait(full + 8 * s, (i >> 3) & 1);
      if (i == 0) TS(8, 6);
      wg_fence();
#pragma unroll
      for (int kk = 0; kk < 4; kk++) wg_ss88_t(acc, dAs + s * 1024 + kk * 2, dB88 + s * 704 + kk * 16, 1);
      wg_commit();
      if (i) { wg_wait<1>(); if (rel) mbar_arrive(empty + ((i - 1) & 7) * 8); }
    }
    wg_wait<0>();
    reg_fence(acc);
    if (rel) mbar_arrive(empty + 56);
    TS(8, 7);
#pragma unroll
    for (int j = 0; j < 22; j++) pk[j] = pack_bf16(acc[2 * j] * ac1[2 * j], acc[2 * j + 1] * ac1[2 * j + 1]);
    put_tile(g_u + (hb * 88 + ct * 11) * 512 + tp, pk);
    bar_arrive(1 + wg, 160);
    TS(9, 0);
    uint32_t gb[8];
#pragma unroll
    for (int j = 0; j < 8; j++) gb[j] = *(const uint32_t*)(g_mod + 2560 + col0 + j * 8);
    float (&ac)[32] = *(float(*)[32])ac1;
    float xf[32], gf[16];
    widen(xf, xr); widen(gf, gb);
#pragma unroll 1
    for (int j = 0; j < 11; j++) {
      const int s = j & 7;
      mbar_wait2(full + 8 * s, j >> 3, fullU + 8 * j);
      if (j == 0) TS(9, 1);
      wg_fence();
#pragma unroll
      for (int kk = 0; kk < 4; kk++) wg_ss64_t(ac, dAh + j * 512 + kk * 128, dB64 + s * 1024 + wg * 512 + kk * 128, (j | kk) != 0);
      wg_commit();
      if (j >= 1 && j < 4) { wg_wait<1>(); if (rel) mbar_arrive(empty + (j - 1) * 8); }
    }
    wg_wait<0>();
    reg_fence(ac);
    TS(9, 2);
    gate_add(xr, xf, gf, ac);
#pragma unroll
    for (int j = 0; j < 8; j += 2)
      stsm4(sA + 49152 + warp * 2048 + (lane & 15) * 128 + (((j + (lane >> 4)) ^ (lane & 7)) << 4), xr[2 * j], xr[2 * j + 1], xr[2 * j + 2], xr[2 * j + 3]);
    fence_async_smem();
    __syncwarp();
    if (lane == 0) {
      asm volatile("cp.async.bulk.tensor.2d.global.shared::cta.bulk_group [%0, {%1, %2}], [%3];" ::"l"(&tmOut), "r"(co * 64), "r"(ho * 64 + (warp & 3) * 16), "r"(sA + 49152 + warp * 2048) : "memory");
      asm volatile("cp.async.bulk.commit_group;" ::: "memory");
      asm volatile("cp.async.bulk.wait_group.read 0;" ::: "memory");
    }
    TS(3, 5);
  }
}

typedef CUresult (*EncodeFn)(CUtensorMap*, CUtensorMapDataType, cuuint32_t, void*, const cuuint64_t*, const cuuint64_t*, const cuuint32_t*,
                             const cuuint32_t*, CUtensorMapInterleave, CUtensorMapSwizzle, CUtensorMapL2promotion, CUtensorMapFloatOOBfill);
static void make_map(EncodeFn fn, CUtensorMap* m, const void* p, uint64_t inner, uint64_t outer, uint32_t bi, uint32_t bo, CUtensorMapSwizzle sw = CU_TENSOR_MAP_SWIZZLE_128B) {
  cuuint64_t dims[2] = {inner, outer}, strides[1] = {inner * 2};
  cuuint32_t box[2] = {bi, bo}, es[2] = {1, 1};
  fn(m, CU_TENSOR_MAP_DATA_TYPE_BFLOAT16, 2, (void*)p, dims, strides, box, es, CU_TENSOR_MAP_INTERLEAVE_NONE, sw,
     CU_TENSOR_MAP_L2_PROMOTION_L2_256B, CU_TENSOR_MAP_FLOAT_OOB_FILL_NONE);
}
template <typename... KA, typename... A>
static void launch(void (*k)(KA...), int grid, int block, int smem, bool pdl, A... args) {
  cudaLaunchConfig_t cfg = {};
  cfg.gridDim = dim3(grid); cfg.blockDim = dim3(block); cfg.dynamicSmemBytes = smem; cfg.stream = cudaStreamPerThread;
  cudaLaunchAttribute at[1];
  at[0].id = cudaLaunchAttributeProgrammaticStreamSerialization; at[0].val.programmaticStreamSerializationAllowed = 1;
  cfg.attrs = at; cfg.numAttrs = pdl ? 1 : 0;
  cudaLaunchKernelEx(&cfg, k, args...);
}

extern "C" void kernel_launch(void* const* d_in, const int* in_sizes, int n_in, void* d_out, int out_size) {
  const bf16* x = (const bf16*)d_in[0]; const bf16* wqkv = (const bf16*)d_in[1]; const bf16* wo = (const bf16*)d_in[2];
  const bf16* w_in = (const bf16*)d_in[4]; const bf16* w_sp = (const bf16*)d_in[5]; const bf16* b_sp = (const bf16*)d_in[6];
  const bf16* w_out = (const bf16*)d_in[7]; const bf16* c = (const bf16*)d_in[8]; const bf16* w_mod = (const bf16*)d_in[9];
  static EncodeFn fn = nullptr;
  static int nsm = 0;
  if (!fn) {
    cudaDeviceGetAttribute(&nsm, cudaDevAttrMultiProcessorCount, 0);
    cudaDriverEntryPointQueryResult qr;
    cudaGetDriverEntryPoint("cuTensorMapEncodeTiled", (void**)&fn, cudaEnableDefault, &qr);
    cudaFuncSetAttribute(k_qkv, cudaFuncAttributeMaxDynamicSharedMemorySize, QKV_SMEM);
    cudaFuncSetAttribute(k_attn, cudaFuncAttributeMaxDynamicSharedMemorySize, ATT_SMEM);
    cudaFuncSetAttribute(k_post, cudaFuncAttributeMaxDynamicSharedMemorySize, POST_SMEM);
  }
  CUtensorMap mX, mQ, mO, mS, mW, mY;
  make_map(fn, &mX, x, 512, 2048, 64, 128);
  make_map(fn, &mQ, wqkv, 1536, 512, 64, 64);
  make_map(fn, &mO, wo, 512, 512, 64, 256);
  make_map(fn, &mS, w_sp, 2048, 2048, 64, 128);
  make_map(fn, &mY, d_out, 512, 2048, 64, 16);
  make_map(fn, &mW, w_out, 512, FH, 64, 64);
  launch(k_qkv, 128, 288, QKV_SMEM, false, x, c, w_mod, wqkv, mX, mQ);
  AttOff off;
  for (int i = 0; i < 2; i++) off.k[i] = 64 * (i + 1);
  for (int i = 0; i < 8; i++) off.v[i] = 16 * i;
  launch(k_attn, 132, 512, ATT_SMEM, true, c, w_mod, w_in, w_sp, w_out, wo, off);
  launch(k_post, nsm == 132 ? 132 : 128, 384, POST_SMEM, true, x, b_sp, mO, mS, mW, mY);
}
```
